```python
import torch

def _softmax(x, axis=-1):
    return torch.softmax(x, dim=axis)

def _gelu(x):
    return torch.nn.functional.gelu(x, approximate='tanh')

def _silu(x):
    return torch.nn.functional.silu(x)

def _sigmoid(x):
    return torch.sigmoid(x)

def _layernorm(x, axis=-1, eps=1e-05):
    m = x.mean(dim=axis, keepdim=True)
    v = x.var(dim=axis, keepdim=True, unbiased=False)
    return (x - m) / torch.sqrt(v + eps)

def _scatter_add(tgt, idx, src, axis=0):
    return tgt.clone().index_add_(axis, idx, src)

def _segment_sum(src, seg, n):
    out = torch.zeros((n,) + src.shape[1:], dtype=src.dtype)
    return out.index_add_(0, seg, src)

def _pad(x, pw):
    flat = tuple((v for pair in reversed(pw) for v in pair))
    return torch.nn.functional.pad(x, flat)
kernel_name = 'gated_mix__sliding_block__memory_aug_recurrent_mem_tr__prompt'

def setup_inputs():

    _w = lambda a: (lambda t: t.to(torch.bfloat16) if t.is_floating_point() else t)(torch.as_tensor(a))

    def _A_setup():
        B, S, D = (1, 2048, 448)
        return {'x': _w((lambda *s: torch.randn(*s, dtype=torch.bfloat16) * 0.05)(B, S, D)), 'wqkv': _w((lambda *s: torch.randn(*s, dtype=torch.bfloat16) * 1.6)(D, 3 * D)), 'wo': _w((lambda *s: torch.randn(*s, dtype=torch.bfloat16) * 0.05)(D, D))}
    _A_in = _A_setup()

    def _B_setup():
        B, S, Dm = (1, 2048, 448)
        H, Dh = (16, 256)
        M, seg = (8, 32)
        seg = min(seg, S)
        S = S // seg * seg
        return {'x': _w((lambda *s: torch.randn(*s, dtype=torch.bfloat16) * 0.05)(B, S, Dm)), 'mem0': _w((lambda *s: torch.randn(*s, dtype=torch.bfloat16) * 1.6)(B, M, Dm)), 'Wq': _w((lambda *s: torch.randn(*s, dtype=torch.bfloat16) * 0.8)(Dm, H, Dh) * Dm ** (-0.5)), 'Wk': _w((lambda *s: torch.randn(*s, dtype=torch.bfloat16) * 0.8)(Dm, H, Dh) * Dm ** (-0.5)), 'Wv': _w((lambda *s: torch.randn(*s, dtype=torch.bfloat16) * 1.6)(Dm, H, Dh) * Dm ** (-0.5)), 'Wo': _w((lambda *s: torch.randn(*s, dtype=torch.bfloat16) * 1.6)(H, Dh, Dm) * (H * Dh) ** (-0.5)), 'seg_len': seg}
    _B_in = _B_setup()
    return {'A_x': _A_in['x'], 'A_wqkv': _A_in['wqkv'], 'A_wo': _A_in['wo'], 'B_x': _B_in['x'], 'B_mem0': _B_in['mem0'], 'B_Wq': _B_in['Wq'], 'B_Wk': _B_in['Wk'], 'B_Wv': _B_in['Wv'], 'B_Wo': _B_in['Wo'], 'B_seg_len': _B_in['seg_len'], 'gate_w': _w((lambda *s: torch.randn(*s, dtype=torch.bfloat16) * 0.05)(448) * 16.0)}

def reference(A_x, A_wqkv, A_wo, B_x, B_mem0, B_Wq, B_Wk, B_Wv, B_Wo, B_seg_len, gate_w):

    def _A_ref(x, wqkv, wo):
        B, S, D = x.shape
        H = 16
        Dh = D // H
        W = 256
        qkv = (lambda x, *d: x.permute(*d))((x @ wqkv).reshape(B, S, 3, H, Dh), 2, 0, 3, 1, 4)
        q, k, v = (qkv[0], qkv[1], qkv[2])
        scores = torch.einsum('bhqd,bhkd->bhqk', q, k) * Dh ** (-0.5)
        idx = torch.arange(S)
        mask = (idx[:, None] - idx[None, :] >= 0) & (idx[:, None] - idx[None, :] < W)
        scores = torch.where(mask[None, None], scores, -1000000000.0)
        p = _softmax(scores, axis=-1)
        o = torch.einsum('bhqk,bhkd->bhqd', p, v)
        return (lambda x, *d: x.permute(*d))(o, 0, 2, 1, 3).reshape(B, S, D) @ wo

    def _B_ref(x, mem0, Wq, Wk, Wv, Wo, seg_len):
        B, S, Dm = x.shape
        H, Dh = (Wq.shape[1], Wq.shape[2])
        M = mem0.shape[1]
        scale = Dh ** (-0.5)
        n_seg = S // seg_len
        L = M + seg_len
        idx = torch.arange(L)
        mask = (idx[:, None] < M) | (idx[:, None] >= idx[None, :])
        mem = mem0
        outs = []
        for s in range(n_seg):
            xs = x[:, s * seg_len:(s + 1) * seg_len, :].clone()
            h = torch.concatenate([mem, xs], axis=1)
            q = torch.einsum('btd,dhe->bhte', h, Wq)
            k = torch.einsum('btd,dhe->bhte', h, Wk)
            v = torch.einsum('btd,dhe->bhte', h, Wv)
            scores = torch.einsum('bhqe,bhke->bhqk', q, k) * scale
            scores = torch.where(mask[None, None], scores, -1000000000.0)
            p = _softmax(scores, axis=-1)
            o = torch.einsum('bhqk,bhke->bhqe', p, v)
            o = torch.einsum('bhte,hed->btd', o, Wo)
            mem = o[:, :M, :].clone()
            outs.append(o[:, M:, :])
        return torch.concatenate(outs, axis=1)
    x = A_x
    g = _sigmoid((x * gate_w).sum(-1, keepdims=True))
    a = _A_ref(x, A_wqkv, A_wo)
    b = _B_ref(x, B_mem0, B_Wq, B_Wk, B_Wv, B_Wo, B_seg_len)
    return g * a + (1 - g) * b
```

```cpp
#include <cuda_runtime.h>
#include <cuda_bf16.h>
#include <cuda.h>
#include <stdint.h>
#include <new>
#include <stdlib.h>
#include <type_traits>

namespace gm {

constexpr int S_    = 2048;
constexpr int D_    = 448;
constexpr int NH    = 16;
constexpr int NSEG  = 64;
constexpr int SEGL  = 32;
constexpr int MTOK  = 8;
constexpr float LOG2E = 1.4426950408889634f;

typedef __nv_bfloat16 bf16;

__device__ __align__(1024) uint32_t gAt[NH * 56 * 56 * 32];
__device__ __align__(1024) uint32_t gBt[NH * 28 * 28 * 128];
__device__ __align__(1024) uint32_t gMem[NSEG * 4 * MTOK * 64];
__device__ __align__(1024) uint4    gVx[NSEG * NH * 28 * 2 * 32];
__device__ __align__(1024) uint2    gVm[NSEG * NH * 28 * 32];
__device__ __align__(1024) uint4    gS[2 * NH * 4 * 80];
__device__ __align__(1024) uint32_t gP[NSEG * NH * 2 * 320];
__device__ __align__(1024) bf16     gQKV[S_ * 3 * NH * 32];
__device__ __align__(1024) bf16     gO[S_ * D_];
__device__ __align__(1024) bf16     gA[S_ * D_];
__device__ __align__(1024) float    gG[S_];
constexpr int F_V   = 0;
constexpr int F_VM  = 16;
constexpr int F_Q   = 80;
constexpr int F_O   = 96;
constexpr int F_A   = 112;
constexpr int F_P   = 128;
constexpr int F_CTR = 144;
constexpr int F_PRE = 145;
constexpr int F_MEM = 160;
constexpr int NFLAGS = 224;
__device__ __align__(128) uint32_t gFlags[NFLAGS * 32];

#define TS(k, i) do { } while (0)
#define TSX(k, b, i) do { } while (0)
#define TSK(k, i) do { } while (0)
#define TSC(k, i, cond) do { } while (0)
__device__ __forceinline__ uint32_t smem_u32(const void* p) { return (uint32_t)__cvta_generic_to_shared(p); }
__device__ __forceinline__ uint32_t pack_bf16(float lo, float hi) {
  uint32_t r; asm("cvt.rn.bf16x2.f32 %0,%1,%2;" : "=r"(r) : "f"(hi), "f"(lo)); return r;
}
__device__ __forceinline__ void mbar_init(uint32_t bar, uint32_t cnt) {
  asm volatile("mbarrier.init.shared::cta.b64 [%0],%1;" ::"r"(bar), "r"(cnt) : "memory");
}
__device__ __forceinline__ void mbar_expect_tx(uint32_t bar, uint32_t bytes) {
  asm volatile("mbarrier.arrive.expect_tx.shared::cta.b64 _,[%0],%1;" ::"r"(bar), "r"(bytes) : "memory");
}
__device__ __forceinline__ void mbar_arrive(uint32_t bar) {
  asm volatile("mbarrier.arrive.shared::cta.b64 _,[%0];" ::"r"(bar) : "memory");
}
#define GM_ABORT() do { *(volatile int*)8 = 0; } while (0)
__device__ __forceinline__ void mbar_wait(uint32_t bar, uint32_t parity) {
  uint32_t ok; int guard = 0;
  do {
    asm volatile("{.reg .pred p; mbarrier.try_wait.parity.shared::cta.b64 p,[%1],%2; selp.u32 %0,1,0,p;}"
                 : "=r"(ok) : "r"(bar), "r"(parity) : "memory");
    if (!ok && ++guard > (1 << 22)) { GM_ABORT(); break; }
  } while (!ok);
}
__device__ __forceinline__ void mbar_wait_cl(uint32_t bar, uint32_t parity) {
  uint32_t ok; int guard = 0;
  do {
    asm volatile("{.reg .pred p; mbarrier.try_wait.parity.acquire.cluster.shared::cta.b64 p,[%1],%2; selp.u32 %0,1,0,p;}"
                 : "=r"(ok) : "r"(bar), "r"(parity) : "memory");
    if (!ok && ++guard > (1 << 22)) { GM_ABORT(); break; }
  } while (!ok);
}
__device__ __forceinline__ void fence_mbar_init() { asm volatile("fence.mbarrier_init.release.cluster;" ::: "memory"); }
__device__ __forceinline__ void fence_proxy_async() { asm volatile("fence.proxy.async;" ::: "memory"); }
__device__ __forceinline__ void fence_proxy_async_global() { asm volatile("fence.proxy.async.global;" ::: "memory"); }
__device__ __forceinline__ void fence_proxy_async_smem() { asm volatile("fence.proxy.async.shared::cta;" ::: "memory"); }
__device__ __forceinline__ void bar_sync(int id, int n) { asm volatile("bar.sync %0,%1;" ::"r"(id), "r"(n) : "memory"); }
__device__ __forceinline__ void bar_arrive(int id, int n) { asm volatile("bar.arrive %0,%1;" ::"r"(id), "r"(n) : "memory"); }
__device__ __forceinline__ void cluster_sync() {
  asm volatile("barrier.cluster.arrive.relaxed.aligned;\n barrier.cluster.wait.aligned;" ::: "memory");
}
__device__ __forceinline__ uint32_t mapa(uint32_t a, uint32_t rank) {
  uint32_t o; asm("mapa.shared::cluster.u32 %0,%1,%2;" : "=r"(o) : "r"(a), "r"(rank)); return o;
}
__device__ __forceinline__ void st_async16(uint32_t addr, uint32_t a, uint32_t b, uint32_t c, uint32_t d, uint32_t bar) {
  asm volatile("st.async.weak.shared::cluster.mbarrier::complete_tx::bytes.v4.b32 [%0],{%1,%2,%3,%4},[%5];"
               ::"r"(addr), "r"(a), "r"(b), "r"(c), "r"(d), "r"(bar) : "memory");
}
__device__ __forceinline__ void st_async8(uint32_t addr, uint32_t a, uint32_t b, uint32_t bar) {
  asm volatile("st.async.weak.shared::cluster.mbarrier::complete_tx::bytes.v2.b32 [%0],{%1,%2},[%3];"
               ::"r"(addr), "r"(a), "r"(b), "r"(bar) : "memory");
}
__device__ __forceinline__ void tma2d(uint32_t dst, const CUtensorMap* m, int c0, int c1, uint32_t bar) {
  asm volatile("cp.async.bulk.tensor.2d.shared::cluster.global.mbarrier::complete_tx::bytes [%0],[%1,{%3,%4}],[%2];"
               ::"r"(dst), "l"(m), "r"(bar), "r"(c0), "r"(c1) : "memory");
}
__device__ __forceinline__ void tma2d_mc(uint32_t dst, const CUtensorMap* m, int c0, int c1, uint32_t bar, uint16_t mask) {
  asm volatile("cp.async.bulk.tensor.2d.shared::cluster.global.mbarrier::complete_tx::bytes.multicast::cluster [%0],[%1,{%3,%4}],[%2],%5;"
               ::"r"(dst), "l"(m), "r"(bar), "r"(c0), "r"(c1), "h"(mask) : "memory");
}
__device__ __forceinline__ void tma2d_store(const CUtensorMap* m, uint32_t src, int c0, int c1) {
  asm volatile("cp.async.bulk.tensor.2d.global.shared::cta.bulk_group [%0,{%2,%3}],[%1];"
               ::"l"(m), "r"(src), "r"(c0), "r"(c1) : "memory");
}
__device__ __forceinline__ void bulk_commit() { asm volatile("cp.async.bulk.commit_group;" ::: "memory"); }
template <int N> __device__ __forceinline__ void bulk_wait_read() { asm volatile("cp.async.bulk.wait_group.read %0;" ::"n"(N) : "memory"); }
template <int N> __device__ __forceinline__ void bulk_wait() { asm volatile("cp.async.bulk.wait_group %0;" ::"n"(N) : "memory"); }
__device__ __forceinline__ void bulk_g2s(uint32_t dst, const void* src, uint32_t bytes, uint32_t bar) {
  asm volatile("cp.async.bulk.shared::cluster.global.mbarrier::complete_tx::bytes [%0],[%1],%2,[%3];"
               ::"r"(dst), "l"(src), "r"(bytes), "r"(bar) : "memory");
}
__device__ __forceinline__ void bulk_s2g(const void* dst, uint32_t src, uint32_t bytes) {
  asm volatile("cp.async.bulk.global.shared::cta.bulk_group [%0],[%1],%2;" ::"l"(dst), "r"(src), "r"(bytes) : "memory");
}
__device__ __forceinline__ void mbar_arrive_remote(uint32_t bar_cluster_addr) {
  asm volatile("mbarrier.arrive.shared::cluster.b64 _,[%0];" ::"r"(bar_cluster_addr) : "memory");
}
__device__ __forceinline__ void cp_async16(uint32_t dst, const void* src) {
  asm volatile("cp.async.cg.shared.global [%0],[%1],16;" ::"r"(dst), "l"(src) : "memory");
}
__device__ __forceinline__ void cp_async_wait_all() { asm volatile("cp.async.wait_all;" ::: "memory"); }
__device__ __forceinline__ void prefetch_tmap(const CUtensorMap* m) {
  asm volatile("prefetch.tensormap [%0];" ::"l"(m) : "memory");
}
__device__ __forceinline__ void ldsm4(uint32_t a, uint32_t& r0, uint32_t& r1, uint32_t& r2, uint32_t& r3) {
  asm volatile("ldmatrix.sync.aligned.m8n8.x4.shared.b16 {%0,%1,%2,%3},[%4];" : "=r"(r0), "=r"(r1), "=r"(r2), "=r"(r3) : "r"(a) : "memory");
}
__device__ __forceinline__ uint4 ldsm128(uint32_t a) { uint4 v; ldsm4(a, v.x, v.y, v.z, v.w); return v; }
__device__ __forceinline__ void ldsm4t(uint32_t a, uint32_t& r0, uint32_t& r1, uint32_t& r2, uint32_t& r3) {
  asm volatile("ldmatrix.sync.aligned.m8n8.x4.trans.shared.b16 {%0,%1,%2,%3},[%4];" : "=r"(r0), "=r"(r1), "=r"(r2), "=r"(r3) : "r"(a) : "memory");
}
__device__ __forceinline__ void ldsm2(uint32_t a, uint32_t& r0, uint32_t& r1) {
  asm volatile("ldmatrix.sync.aligned.m8n8.x2.shared.b16 {%0,%1},[%2];" : "=r"(r0), "=r"(r1) : "r"(a) : "memory");
}
__device__ __forceinline__ void stsm4(uint32_t a, uint32_t r0, uint32_t r1, uint32_t r2, uint32_t r3) {
  asm volatile("stmatrix.sync.aligned.m8n8.x4.shared.b16 [%0],{%1,%2,%3,%4};" ::"r"(a), "r"(r0), "r"(r1), "r"(r2), "r"(r3) : "memory");
}
__device__ __forceinline__ void stsm2(uint32_t a, uint32_t r0, uint32_t r1) {
  asm volatile("stmatrix.sync.aligned.m8n8.x2.shared.b16 [%0],{%1,%2};" ::"r"(a), "r"(r0), "r"(r1) : "memory");
}
__device__ __forceinline__ uint32_t movm(uint32_t a) {
  uint32_t r; asm volatile("movmatrix.sync.aligned.m8n8.trans.b16 %0,%1;" : "=r"(r) : "r"(a)); return r;
}
__device__ __forceinline__ void mma16816(float (&c)[4], uint32_t a0, uint32_t a1, uint32_t a2, uint32_t a3, uint32_t b0, uint32_t b1) {
  asm volatile("mma.sync.aligned.m16n8k16.row.col.f32.bf16.bf16.f32 {%0,%1,%2,%3},{%4,%5,%6,%7},{%8,%9},{%0,%1,%2,%3};"
               : "+f"(c[0]), "+f"(c[1]), "+f"(c[2]), "+f"(c[3]) : "r"(a0), "r"(a1), "r"(a2), "r"(a3), "r"(b0), "r"(b1));
}
__device__ __forceinline__ void mma1688(float (&c)[4], uint32_t a0, uint32_t a1, uint32_t b0) {
  asm volatile("mma.sync.aligned.m16n8k8.row.col.f32.bf16.bf16.f32 {%0,%1,%2,%3},{%4,%5},{%6},{%0,%1,%2,%3};"
               : "+f"(c[0]), "+f"(c[1]), "+f"(c[2]), "+f"(c[3]) : "r"(a0), "r"(a1), "r"(b0));
}
__device__ __forceinline__ uint4 lds128(uint32_t a) {
  uint4 v; asm volatile("ld.shared.v4.u32 {%0,%1,%2,%3},[%4];" : "=r"(v.x), "=r"(v.y), "=r"(v.z), "=r"(v.w) : "r"(a) : "memory"); return v;
}
__device__ __forceinline__ uint2 lds64(uint32_t a) {
  uint2 v; asm volatile("ld.shared.v2.u32 {%0,%1},[%2];" : "=r"(v.x), "=r"(v.y) : "r"(a) : "memory"); return v;
}
__device__ __forceinline__ uint32_t lds32(uint32_t a) {
  uint32_t v; asm volatile("ld.shared.u32 %0,[%1];" : "=r"(v) : "r"(a) : "memory"); return v;
}
__device__ __forceinline__ void sts128(uint32_t a, uint32_t x, uint32_t y, uint32_t z, uint32_t w) {
  asm volatile("st.shared.v4.u32 [%0],{%1,%2,%3,%4};" ::"r"(a), "r"(x), "r"(y), "r"(z), "r"(w) : "memory");
}
__device__ __forceinline__ void sts64(uint32_t a, uint32_t x, uint32_t y) {
  asm volatile("st.shared.v2.u32 [%0],{%1,%2};" ::"r"(a), "r"(x), "r"(y) : "memory");
}
__device__ __forceinline__ void sts32(uint32_t a, uint32_t x) { asm volatile("st.shared.u32 [%0],%1;" ::"r"(a), "r"(x) : "memory"); }
__device__ __forceinline__ uint4 ldg_relaxed128(const void* p) {
  uint4 v; asm volatile("ld.relaxed.gpu.global.v4.u32 {%0,%1,%2,%3},[%4];" : "=r"(v.x), "=r"(v.y), "=r"(v.z), "=r"(v.w) : "l"(p) : "memory"); return v;
}
__device__ __forceinline__ void stg_relaxed128(void* p, uint32_t x, uint32_t y, uint32_t z, uint32_t w) {
  asm volatile("st.relaxed.gpu.global.v4.u32 [%0],{%1,%2,%3,%4};" ::"l"(p), "r"(x), "r"(y), "r"(z), "r"(w) : "memory");
}
__device__ __forceinline__ void stg_relaxed64(void* p, uint32_t x, uint32_t y) {
  asm volatile("st.relaxed.gpu.global.v2.u32 [%0],{%1,%2};" ::"l"(p), "r"(x), "r"(y) : "memory");
}
__device__ __forceinline__ void stg_relaxed32(void* p, uint32_t x) {
  asm volatile("st.relaxed.gpu.global.u32 [%0],%1;" ::"l"(p), "r"(x) : "memory");
}
__device__ __forceinline__ uint32_t ld_acquire(const uint32_t* p) {
  uint32_t v; asm volatile("ld.acquire.gpu.global.u32 %0,[%1];" : "=r"(v) : "l"(p) : "memory"); return v;
}
__device__ __forceinline__ void red_release_add(uint32_t* p, uint32_t v) {
  asm volatile("red.release.gpu.global.add.u32 [%0],%1;" ::"l"(p), "r"(v) : "memory");
}
__device__ __forceinline__ void red_relaxed_add(uint32_t* p, uint32_t v) {
  asm volatile("red.relaxed.gpu.global.add.u32 [%0],%1;" ::"l"(p), "r"(v) : "memory");
}
template <int NS = 100>
__device__ __forceinline__ void flag_wait(const uint32_t* p, uint32_t target) {
  int guard = 0;
  while (ld_acquire(p) < target) { if (++guard > (1 << 21)) { GM_ABORT(); break; } __nanosleep(NS); }
}
__device__ __forceinline__ void prefetch_l2(const void* p) { asm volatile("prefetch.global.L2 [%0];" ::"l"(p) : "memory"); }
#define KEEP(x) asm volatile("" : "+r"(x))
#define KEEPP(x) asm volatile("" : "+l"(x))
__device__ __forceinline__ uint32_t ldg_relaxed32(const void* p) {
  uint32_t v; asm volatile("ld.relaxed.gpu.global.u32 %0,[%1];" : "=r"(v) : "l"(p) : "memory"); return v;
}
__device__ __forceinline__ float ex2(float x) { float y; asm("ex2.approx.ftz.f32 %0,%1;" : "=f"(y) : "f"(x)); return y; }
__device__ __forceinline__ float rcp(float x) { float y; asm("rcp.approx.ftz.f32 %0,%1;" : "=f"(y) : "f"(x)); return y; }

__device__ __forceinline__ void wg_fence() { asm volatile("wgmma.fence.sync.aligned;" ::: "memory"); }
__device__ __forceinline__ void wg_commit() { asm volatile("wgmma.commit_group.sync.aligned;" ::: "memory"); }
template <int N> __device__ __forceinline__ void wg_wait() { asm volatile("wgmma.wait_group.sync.aligned %0;" ::"n"(N) : "memory"); }
__device__ __forceinline__ uint64_t make_desc_ns(uint32_t saddr, uint32_t lbo_bytes, uint32_t sbo_bytes) {
  return (uint64_t)((saddr & 0x3FFFF) >> 4) | ((uint64_t)(lbo_bytes >> 4) << 16) | ((uint64_t)(sbo_bytes >> 4) << 32);
}
__device__ __forceinline__ uint64_t make_desc(uint32_t saddr, uint32_t lbo_bytes) {
  return (uint64_t)((saddr & 0x3FFFF) >> 4) | ((uint64_t)(lbo_bytes >> 4) << 16) | ((uint64_t)(1024 >> 4) << 32) | ((uint64_t)1 << 62);
}
template <int N> __device__ __forceinline__ void reg_fence(float (&d)[N]) {
#pragma unroll
  for (int i = 0; i < N; i++) asm volatile("" : "+f"(d[i])::"memory");
}
__device__ __forceinline__ void pdl_wait() { asm volatile("griddepcontrol.wait;" ::: "memory"); }
__device__ __forceinline__ void pdl_launch() { asm volatile("griddepcontrol.launch_dependents;" ::: "memory"); }

template<int TA,int TB> __device__ __forceinline__ void wg_ss_n112(float (&d)[56], uint64_t da, uint64_t db, int sd){
  asm volatile("{.reg .pred p; setp.ne.b32 p,%58,0;\n"
   "wgmma.mma_async.sync.aligned.m64n112k16.f32.bf16.bf16 {%0,%1,%2,%3,%4,%5,%6,%7,%8,%9,%10,%11,%12,%13,%14,%15,%16,%17,%18,%19,%20,%21,%22,%23,%24,%25,%26,%27,%28,%29,%30,%31,%32,%33,%34,%35,%36,%37,%38,%39,%40,%41,%42,%43,%44,%45,%46,%47,%48,%49,%50,%51,%52,%53,%54,%55},%56,%57,p,1,1,%59,%60;}\n"
   :"+f"(d[0]),"+f"(d[1]),"+f"(d[2]),"+f"(d[3]),"+f"(d[4]),"+f"(d[5]),"+f"(d[6]),"+f"(d[7]),"+f"(d[8]),"+f"(d[9]),"+f"(d[10]),"+f"(d[11]),"+f"(d[12]),"+f"(d[13]),"+f"(d[14]),"+f"(d[15]),"+f"(d[16]),"+f"(d[17]),"+f"(d[18]),"+f"(d[19]),"+f"(d[20]),"+f"(d[21]),"+f"(d[22]),"+f"(d[23]),"+f"(d[24]),"+f"(d[25]),"+f"(d[26]),"+f"(d[27]),"+f"(d[28]),"+f"(d[29]),"+f"(d[30]),"+f"(d[31]),"+f"(d[32]),"+f"(d[33]),"+f"(d[34]),"+f"(d[35]),"+f"(d[36]),"+f"(d[37]),"+f"(d[38]),"+f"(d[39]),"+f"(d[40]),"+f"(d[41]),"+f"(d[42]),"+f"(d[43]),"+f"(d[44]),"+f"(d[45]),"+f"(d[46]),"+f"(d[47]),"+f"(d[48]),"+f"(d[49]),"+f"(d[50]),"+f"(d[51]),"+f"(d[52]),"+f"(d[53]),"+f"(d[54]),"+f"(d[55])
   :"l"(da),"l"(db),"r"(sd),"n"(TA),"n"(TB));
}
template<int TA,int TB> __device__ __forceinline__ void wg_ss_n192(float (&d)[96], uint64_t da, uint64_t db, int sd){
  asm volatile("{.reg .pred p; setp.ne.b32 p,%98,0;\n"
   "wgmma.mma_async.sync.aligned.m64n192k16.f32.bf16.bf16 {%0,%1,%2,%3,%4,%5,%6,%7,%8,%9,%10,%11,%12,%13,%14,%15,%16,%17,%18,%19,%20,%21,%22,%23,%24,%25,%26,%27,%28,%29,%30,%31,%32,%33,%34,%35,%36,%37,%38,%39,%40,%41,%42,%43,%44,%45,%46,%47,%48,%49,%50,%51,%52,%53,%54,%55,%56,%57,%58,%59,%60,%61,%62,%63,%64,%65,%66,%67,%68,%69,%70,%71,%72,%73,%74,%75,%76,%77,%78,%79,%80,%81,%82,%83,%84,%85,%86,%87,%88,%89,%90,%91,%92,%93,%94,%95},%96,%97,p,1,1,%99,%100;}\n"
   :"+f"(d[0]),"+f"(d[1]),"+f"(d[2]),"+f"(d[3]),"+f"(d[4]),"+f"(d[5]),"+f"(d[6]),"+f"(d[7]),"+f"(d[8]),"+f"(d[9]),"+f"(d[10]),"+f"(d[11]),"+f"(d[12]),"+f"(d[13]),"+f"(d[14]),"+f"(d[15]),"+f"(d[16]),"+f"(d[17]),"+f"(d[18]),"+f"(d[19]),"+f"(d[20]),"+f"(d[21]),"+f"(d[22]),"+f"(d[23]),"+f"(d[24]),"+f"(d[25]),"+f"(d[26]),"+f"(d[27]),"+f"(d[28]),"+f"(d[29]),"+f"(d[30]),"+f"(d[31]),"+f"(d[32]),"+f"(d[33]),"+f"(d[34]),"+f"(d[35]),"+f"(d[36]),"+f"(d[37]),"+f"(d[38]),"+f"(d[39]),"+f"(d[40]),"+f"(d[41]),"+f"(d[42]),"+f"(d[43]),"+f"(d[44]),"+f"(d[45]),"+f"(d[46]),"+f"(d[47]),"+f"(d[48]),"+f"(d[49]),"+f"(d[50]),"+f"(d[51]),"+f"(d[52]),"+f"(d[53]),"+f"(d[54]),"+f"(d[55]),"+f"(d[56]),"+f"(d[57]),"+f"(d[58]),"+f"(d[59]),"+f"(d[60]),"+f"(d[61]),"+f"(d[62]),"+f"(d[63]),"+f"(d[64]),"+f"(d[65]),"+f"(d[66]),"+f"(d[67]),"+f"(d[68]),"+f"(d[69]),"+f"(d[70]),"+f"(d[71]),"+f"(d[72]),"+f"(d[73]),"+f"(d[74]),"+f"(d[75]),"+f"(d[76]),"+f"(d[77]),"+f"(d[78]),"+f"(d[79]),"+f"(d[80]),"+f"(d[81]),"+f"(d[82]),"+f"(d[83]),"+f"(d[84]),"+f"(d[85]),"+f"(d[86]),"+f"(d[87]),"+f"(d[88]),"+f"(d[89]),"+f"(d[90]),"+f"(d[91]),"+f"(d[92]),"+f"(d[93]),"+f"(d[94]),"+f"(d[95])
   :"l"(da),"l"(db),"r"(sd),"n"(TA),"n"(TB));
}
template<int TA,int TB> __device__ __forceinline__ void wg_ss_n224(float (&d)[112], uint64_t da, uint64_t db, int sd){
  asm volatile("{.reg .pred p; setp.ne.b32 p,%114,0;\n"
   "wgmma.mma_async.sync.aligned.m64n224k16.f32.bf16.bf16 {%0,%1,%2,%3,%4,%5,%6,%7,%8,%9,%10,%11,%12,%13,%14,%15,%16,%17,%18,%19,%20,%21,%22,%23,%24,%25,%26,%27,%28,%29,%30,%31,%32,%33,%34,%35,%36,%37,%38,%39,%40,%41,%42,%43,%44,%45,%46,%47,%48,%49,%50,%51,%52,%53,%54,%55,%56,%57,%58,%59,%60,%61,%62,%63,%64,%65,%66,%67,%68,%69,%70,%71,%72,%73,%74,%75,%76,%77,%78,%79,%80,%81,%82,%83,%84,%85,%86,%87,%88,%89,%90,%91,%92,%93,%94,%95,%96,%97,%98,%99,%100,%101,%102,%103,%104,%105,%106,%107,%108,%109,%110,%111},%112,%113,p,1,1,%115,%116;}\n"
   :"+f"(d[0]),"+f"(d[1]),"+f"(d[2]),"+f"(d[3]),"+f"(d[4]),"+f"(d[5]),"+f"(d[6]),"+f"(d[7]),"+f"(d[8]),"+f"(d[9]),"+f"(d[10]),"+f"(d[11]),"+f"(d[12]),"+f"(d[13]),"+f"(d[14]),"+f"(d[15]),"+f"(d[16]),"+f"(d[17]),"+f"(d[18]),"+f"(d[19]),"+f"(d[20]),"+f"(d[21]),"+f"(d[22]),"+f"(d[23]),"+f"(d[24]),"+f"(d[25]),"+f"(d[26]),"+f"(d[27]),"+f"(d[28]),"+f"(d[29]),"+f"(d[30]),"+f"(d[31]),"+f"(d[32]),"+f"(d[33]),"+f"(d[34]),"+f"(d[35]),"+f"(d[36]),"+f"(d[37]),"+f"(d[38]),"+f"(d[39]),"+f"(d[40]),"+f"(d[41]),"+f"(d[42]),"+f"(d[43]),"+f"(d[44]),"+f"(d[45]),"+f"(d[46]),"+f"(d[47]),"+f"(d[48]),"+f"(d[49]),"+f"(d[50]),"+f"(d[51]),"+f"(d[52]),"+f"(d[53]),"+f"(d[54]),"+f"(d[55]),"+f"(d[56]),"+f"(d[57]),"+f"(d[58]),"+f"(d[59]),"+f"(d[60]),"+f"(d[61]),"+f"(d[62]),"+f"(d[63]),"+f"(d[64]),"+f"(d[65]),"+f"(d[66]),"+f"(d[67]),"+f"(d[68]),"+f"(d[69]),"+f"(d[70]),"+f"(d[71]),"+f"(d[72]),"+f"(d[73]),"+f"(d[74]),"+f"(d[75]),"+f"(d[76]),"+f"(d[77]),"+f"(d[78]),"+f"(d[79]),"+f"(d[80]),"+f"(d[81]),"+f"(d[82]),"+f"(d[83]),"+f"(d[84]),"+f"(d[85]),"+f"(d[86]),"+f"(d[87]),"+f"(d[88]),"+f"(d[89]),"+f"(d[90]),"+f"(d[91]),"+f"(d[92]),"+f"(d[93]),"+f"(d[94]),"+f"(d[95]),"+f"(d[96]),"+f"(d[97]),"+f"(d[98]),"+f"(d[99]),"+f"(d[100]),"+f"(d[101]),"+f"(d[102]),"+f"(d[103]),"+f"(d[104]),"+f"(d[105]),"+f"(d[106]),"+f"(d[107]),"+f"(d[108]),"+f"(d[109]),"+f"(d[110]),"+f"(d[111])
   :"l"(da),"l"(db),"r"(sd),"n"(TA),"n"(TB));
}
template<int TA,int TB> __device__ __forceinline__ void wg_ss_n256(float (&d)[128], uint64_t da, uint64_t db, int sd){
  asm volatile("{.reg .pred p; setp.ne.b32 p,%130,0;\n"
   "wgmma.mma_async.sync.aligned.m64n256k16.f32.bf16.bf16 {%0,%1,%2,%3,%4,%5,%6,%7,%8,%9,%10,%11,%12,%13,%14,%15,%16,%17,%18,%19,%20,%21,%22,%23,%24,%25,%26,%27,%28,%29,%30,%31,%32,%33,%34,%35,%36,%37,%38,%39,%40,%41,%42,%43,%44,%45,%46,%47,%48,%49,%50,%51,%52,%53,%54,%55,%56,%57,%58,%59,%60,%61,%62,%63,%64,%65,%66,%67,%68,%69,%70,%71,%72,%73,%74,%75,%76,%77,%78,%79,%80,%81,%82,%83,%84,%85,%86,%87,%88,%89,%90,%91,%92,%93,%94,%95,%96,%97,%98,%99,%100,%101,%102,%103,%104,%105,%106,%107,%108,%109,%110,%111,%112,%113,%114,%115,%116,%117,%118,%119,%120,%121,%122,%123,%124,%125,%126,%127},%128,%129,p,1,1,%131,%132;}\n"
   :"+f"(d[0]),"+f"(d[1]),"+f"(d[2]),"+f"(d[3]),"+f"(d[4]),"+f"(d[5]),"+f"(d[6]),"+f"(d[7]),"+f"(d[8]),"+f"(d[9]),"+f"(d[10]),"+f"(d[11]),"+f"(d[12]),"+f"(d[13]),"+f"(d[14]),"+f"(d[15]),"+f"(d[16]),"+f"(d[17]),"+f"(d[18]),"+f"(d[19]),"+f"(d[20]),"+f"(d[21]),"+f"(d[22]),"+f"(d[23]),"+f"(d[24]),"+f"(d[25]),"+f"(d[26]),"+f"(d[27]),"+f"(d[28]),"+f"(d[29]),"+f"(d[30]),"+f"(d[31]),"+f"(d[32]),"+f"(d[33]),"+f"(d[34]),"+f"(d[35]),"+f"(d[36]),"+f"(d[37]),"+f"(d[38]),"+f"(d[39]),"+f"(d[40]),"+f"(d[41]),"+f"(d[42]),"+f"(d[43]),"+f"(d[44]),"+f"(d[45]),"+f"(d[46]),"+f"(d[47]),"+f"(d[48]),"+f"(d[49]),"+f"(d[50]),"+f"(d[51]),"+f"(d[52]),"+f"(d[53]),"+f"(d[54]),"+f"(d[55]),"+f"(d[56]),"+f"(d[57]),"+f"(d[58]),"+f"(d[59]),"+f"(d[60]),"+f"(d[61]),"+f"(d[62]),"+f"(d[63]),"+f"(d[64]),"+f"(d[65]),"+f"(d[66]),"+f"(d[67]),"+f"(d[68]),"+f"(d[69]),"+f"(d[70]),"+f"(d[71]),"+f"(d[72]),"+f"(d[73]),"+f"(d[74]),"+f"(d[75]),"+f"(d[76]),"+f"(d[77]),"+f"(d[78]),"+f"(d[79]),"+f"(d[80]),"+f"(d[81]),"+f"(d[82]),"+f"(d[83]),"+f"(d[84]),"+f"(d[85]),"+f"(d[86]),"+f"(d[87]),"+f"(d[88]),"+f"(d[89]),"+f"(d[90]),"+f"(d[91]),"+f"(d[92]),"+f"(d[93]),"+f"(d[94]),"+f"(d[95]),"+f"(d[96]),"+f"(d[97]),"+f"(d[98]),"+f"(d[99]),"+f"(d[100]),"+f"(d[101]),"+f"(d[102]),"+f"(d[103]),"+f"(d[104]),"+f"(d[105]),"+f"(d[106]),"+f"(d[107]),"+f"(d[108]),"+f"(d[109]),"+f"(d[110]),"+f"(d[111]),"+f"(d[112]),"+f"(d[113]),"+f"(d[114]),"+f"(d[115]),"+f"(d[116]),"+f"(d[117]),"+f"(d[118]),"+f"(d[119]),"+f"(d[120]),"+f"(d[121]),"+f"(d[122]),"+f"(d[123]),"+f"(d[124]),"+f"(d[125]),"+f"(d[126]),"+f"(d[127])
   :"l"(da),"l"(db),"r"(sd),"n"(TA),"n"(TB));
}
template<int TB> __device__ __forceinline__ void wg_rs_n16(float (&d)[8], uint32_t a0, uint32_t a1, uint32_t a2, uint32_t a3, uint64_t db, int sd){
  asm volatile("{.reg .pred p; setp.ne.b32 p,%13,0;\n"
   "wgmma.mma_async.sync.aligned.m64n16k16.f32.bf16.bf16 {%0,%1,%2,%3,%4,%5,%6,%7},{%8,%9,%10,%11},%12,p,1,1,%14;}\n"
   :"+f"(d[0]),"+f"(d[1]),"+f"(d[2]),"+f"(d[3]),"+f"(d[4]),"+f"(d[5]),"+f"(d[6]),"+f"(d[7])
   :"r"(a0),"r"(a1),"r"(a2),"r"(a3),"l"(db),"r"(sd),"n"(TB));
}
template<int TB> __device__ __forceinline__ void wg_rs_n64(float (&d)[32], uint32_t a0, uint32_t a1, uint32_t a2, uint32_t a3, uint64_t db, int sd){
  asm volatile("{.reg .pred p; setp.ne.b32 p,%37,0;\n"
   "wgmma.mma_async.sync.aligned.m64n64k16.f32.bf16.bf16 {%0,%1,%2,%3,%4,%5,%6,%7,%8,%9,%10,%11,%12,%13,%14,%15,%16,%17,%18,%19,%20,%21,%22,%23,%24,%25,%26,%27,%28,%29,%30,%31},{%32,%33,%34,%35},%36,p,1,1,%38;}\n"
   :"+f"(d[0]),"+f"(d[1]),"+f"(d[2]),"+f"(d[3]),"+f"(d[4]),"+f"(d[5]),"+f"(d[6]),"+f"(d[7]),"+f"(d[8]),"+f"(d[9]),"+f"(d[10]),"+f"(d[11]),"+f"(d[12]),"+f"(d[13]),"+f"(d[14]),"+f"(d[15]),"+f"(d[16]),"+f"(d[17]),"+f"(d[18]),"+f"(d[19]),"+f"(d[20]),"+f"(d[21]),"+f"(d[22]),"+f"(d[23]),"+f"(d[24]),"+f"(d[25]),"+f"(d[26]),"+f"(d[27]),"+f"(d[28]),"+f"(d[29]),"+f"(d[30]),"+f"(d[31])
   :"r"(a0),"r"(a1),"r"(a2),"r"(a3),"l"(db),"r"(sd),"n"(TB));
}
template<int TB> __device__ __forceinline__ void wg_rs_n128(float (&d)[64], uint32_t a0, uint32_t a1, uint32_t a2, uint32_t a3, uint64_t db, int sd){
  asm volatile("{.reg .pred p; setp.ne.b32 p,%69,0;\n"
   "wgmma.mma_async.sync.aligned.m64n128k16.f32.bf16.bf16 {%0,%1,%2,%3,%4,%5,%6,%7,%8,%9,%10,%11,%12,%13,%14,%15,%16,%17,%18,%19,%20,%21,%22,%23,%24,%25,%26,%27,%28,%29,%30,%31,%32,%33,%34,%35,%36,%37,%38,%39,%40,%41,%42,%43,%44,%45,%46,%47,%48,%49,%50,%51,%52,%53,%54,%55,%56,%57,%58,%59,%60,%61,%62,%63},{%64,%65,%66,%67},%68,p,1,1,%70;}\n"
   :"+f"(d[0]),"+f"(d[1]),"+f"(d[2]),"+f"(d[3]),"+f"(d[4]),"+f"(d[5]),"+f"(d[6]),"+f"(d[7]),"+f"(d[8]),"+f"(d[9]),"+f"(d[10]),"+f"(d[11]),"+f"(d[12]),"+f"(d[13]),"+f"(d[14]),"+f"(d[15]),"+f"(d[16]),"+f"(d[17]),"+f"(d[18]),"+f"(d[19]),"+f"(d[20]),"+f"(d[21]),"+f"(d[22]),"+f"(d[23]),"+f"(d[24]),"+f"(d[25]),"+f"(d[26]),"+f"(d[27]),"+f"(d[28]),"+f"(d[29]),"+f"(d[30]),"+f"(d[31]),"+f"(d[32]),"+f"(d[33]),"+f"(d[34]),"+f"(d[35]),"+f"(d[36]),"+f"(d[37]),"+f"(d[38]),"+f"(d[39]),"+f"(d[40]),"+f"(d[41]),"+f"(d[42]),"+f"(d[43]),"+f"(d[44]),"+f"(d[45]),"+f"(d[46]),"+f"(d[47]),"+f"(d[48]),"+f"(d[49]),"+f"(d[50]),"+f"(d[51]),"+f"(d[52]),"+f"(d[53]),"+f"(d[54]),"+f"(d[55]),"+f"(d[56]),"+f"(d[57]),"+f"(d[58]),"+f"(d[59]),"+f"(d[60]),"+f"(d[61]),"+f"(d[62]),"+f"(d[63])
   :"r"(a0),"r"(a1),"r"(a2),"r"(a3),"l"(db),"r"(sd),"n"(TB));
}
struct KPParams {
  CUtensorMap tmWq, tmWk, tmWv, tmWo;
  const bf16* x; const bf16* gate_w; const bf16* mem0;
  const bf16* W[4];
};
constexpr int KP_BQ = 0;
constexpr int KP_RING = 57344;
constexpr int KP_NSL = 5;
constexpr int KP_BAR = KP_RING + KP_NSL * 32768;
constexpr int KP_SMEM = KP_BAR + 128 + 1024;

template <int KIND>
__device__ __forceinline__ void kp_consumer(uint32_t sb, int h, int q, int wg, int w, int lane) {
  const uint32_t bars = sb + KP_BAR;
  TS(9, 0);
  mbar_wait(bars, 0);
  TS(9, 1);
  const int r = lane >> 2, c = lane & 3;
  for (int mt = wg; mt < 7; mt += 2) {
    const int slot = mt % KP_NSL;
    mbar_wait(bars + 8 + slot * 8, (mt / KP_NSL) & 1);
    if (mt == 0) TS(9, 2);
    if (mt == 2) TS(9, 3);
    if (mt == 4) TS(10, 0);
    if (mt == 6) TS(10, 1);
    float acc[56];
    const uint32_t abase = sb + KP_RING + slot * 32768;
    wg_fence();
#pragma unroll
    for (int cc = 0; cc < 4; cc++)
#pragma unroll
      for (int ks = 0; ks < 4; ks++) {
        uint64_t da = make_desc(abase + cc * 8192 + (KIND ? ks * 2048 : ks * 32), 0);
        uint64_t db = make_desc(sb + KP_BQ + cc * 14336 + ks * 32, 0);
        wg_ss_n112<KIND, 0>(acc, da, db, (cc | ks) != 0);
      }
    wg_commit();
    wg_wait<0>();
    reg_fence(acc);
    if (mt == 0) TS(10, 3);
    if (mt < 2 && lane < 2) mbar_arrive_remote(mapa(bars + 48 + slot * 8, lane));
    if (KIND == 0) {
      const float sc = 0.0625f * LOG2E;
      uint32_t* dst = gAt + ((h * 56 + 8 * mt + 2 * (w & 3)) * 56 + 14 * q) * 32 + lane;
#pragma unroll
      for (int jj = 0; jj < 14; jj++) {
        dst[jj * 32] = pack_bf16(acc[4 * jj] * sc, acc[4 * jj + 1] * sc);
        dst[(56 + jj) * 32] = pack_bf16(acc[4 * jj + 2] * sc, acc[4 * jj + 3] * sc);
      }
    } else {
      const int f0 = r, f1 = r + 8;
      const int rho0 = ((f0 & 3) < 2) ? 2 * (f0 >> 2) + (f0 & 3) : 8 + 2 * (f0 >> 2) + (f0 & 3) - 2;
      const int rho1 = ((f1 & 3) < 2) ? 2 * (f1 >> 2) + (f1 & 3) : 8 + 2 * (f1 >> 2) + (f1 & 3) - 2;
      uint32_t* dst = gBt + ((h * 28 + 4 * mt + (w & 3)) * 28 + 7 * q) * 128 + c;
      uint32_t* d0 = dst + (rho0 >> 3) * 32 + (rho0 & 7) * 4;
      uint32_t* d1 = dst + (rho1 >> 3) * 32 + (rho1 & 7) * 4;
#pragma unroll
      for (int jj = 0; jj < 14; jj++) {
        d0[(jj >> 1) * 128 + (jj & 1) * 64] = pack_bf16(acc[4 * jj], acc[4 * jj + 1]);
        d1[(jj >> 1) * 128 + (jj & 1) * 64] = pack_bf16(acc[4 * jj + 2], acc[4 * jj + 3]);
      }
    }
  }
}

__global__ void __launch_bounds__(384, 1) k_pre(const __grid_constant__ KPParams p) {
  extern __shared__ uint8_t smem_raw[];
  const uint32_t sb = (smem_u32(smem_raw) + 1023) & ~1023u;
  const int tid = threadIdx.x, w = tid >> 5, lane = tid & 31;
  const int u = blockIdx.x, kind = u >> 6, h = (u >> 2) & 15, q = u & 3;
  const uint32_t bars = sb + KP_BAR;
  TS(0, 0);
  if (tid == 0) {
    mbar_init(bars, 1);
    for (int i = 0; i < KP_NSL; i++) { mbar_init(bars + 8 + i * 8, 1); mbar_init(bars + 48 + i * 8, 8); }
    fence_mbar_init();
  }
  __syncthreads();
  asm volatile("barrier.cluster.arrive.relaxed.aligned;" ::: "memory");
  if (tid == 256) {
    const CUtensorMap* tb = kind ? &p.tmWv : &p.tmWq;
    mbar_expect_tx(bars, 57344);
    for (int cc = 0; cc < 4; cc++) tma2d(sb + KP_BQ + cc * 14336, tb, h * 256 + 64 * cc, 112 * q, bars);
  }
  __syncwarp();
  asm volatile("barrier.cluster.wait.aligned;" ::: "memory");
  pdl_launch();
  if (w == 8) {
    if (lane == 0) {
      const CUtensorMap* ta = kind ? &p.tmWo : &p.tmWk;
      for (int mt = 0; mt < 7; mt++) {
        const int slot = mt % KP_NSL;
        if (mt >= KP_NSL) mbar_wait(bars + 48 + slot * 8, 0);
        mbar_expect_tx(bars + 8 + slot * 8, 32768);
        for (int cc = 2 * (q & 1); cc < 2 * (q & 1) + 2; cc++) {
          const uint32_t dst = sb + KP_RING + slot * 32768 + cc * 8192;
          if (kind) tma2d_mc(dst, ta, 64 * mt, h * 256 + 64 * cc, bars + 8 + slot * 8, 0x3);
          else      tma2d_mc(dst, ta, h * 256 + 64 * cc, 64 * mt, bars + 8 + slot * 8, 0x3);
        }
      }
    }
  } else if (w > 8) {
    const int gt = u * 96 + (tid - 288);
    for (int i = gt; i < NSEG * 512; i += 128 * 96) {
      uint4 v = make_uint4(~0u, ~0u, ~0u, ~0u);
      if (i < 512 && (i & 15) < 14) v = reinterpret_cast<const uint4*>(p.mem0)[((i >> 4) & 7) * 56 + (i >> 7) * 14 + (i & 15)];
      reinterpret_cast<uint4*>(gMem)[i] = v;
    }
    if (gt < 2 * NH * 4 * 80) gS[gt] = make_uint4(0, 0, 0, 0);
    if (gt < NFLAGS) gFlags[gt * 32] = 0;
    const uint32_t* gw = reinterpret_cast<const uint32_t*>(p.gate_w);
    uint32_t gwr[7];
#pragma unroll
    for (int i = 0; i < 7; i++) gwr[i] = gw[lane + 32 * i];
    for (int tt = w - 9; tt < 16; tt += 3) {
      const int t = u * 16 + tt;
      const uint32_t* xr = reinterpret_cast<const uint32_t*>(p.x + t * D_);
      float s = 0.f;
#pragma unroll
      for (int i = 0; i < 7; i++) {
        const uint32_t a = xr[lane + 32 * i], b = gwr[i];
        float p0 = __uint_as_float(a << 16) * __uint_as_float(b << 16), p1 = __uint_as_float(a & 0xffff0000u) * __uint_as_float(b & 0xffff0000u);
        uint32_t r = pack_bf16(p0, p1);
        s += __uint_as_float(r << 16) + __uint_as_float(r & 0xffff0000u);
      }
#pragma unroll
      for (int o = 16; o; o >>= 1) s += __shfl_xor_sync(~0u, s, o);
      if (lane == 0) {
        float z = __bfloat162float(__float2bfloat16(s));
        gG[t] = __bfloat162float(__float2bfloat16(1.0f / (1.0f + __expf(-z))));
      }
    }
  } else {
    const int wg = w >> 2;
    if (kind) kp_consumer<1>(sb, h, q, wg, w, lane);
    else      kp_consumer<0>(sb, h, q, wg, w, lane);
  }
  __syncthreads();
  TS(10, 2);
  if (tid == 0) red_release_add(&gFlags[F_PRE * 32], 1);
  TS(0, 1);
  cluster_sync();
}

struct KVParams { CUtensorMap tmX64; };
#define KV_NST 12
constexpr int KV_STAGES = KV_NST;
constexpr int KV_BAR = KV_STAGES * 16384;
constexpr int KV_SMEM = KV_BAR + 256 + 1024;
constexpr int KV_WST = 5;
static_assert(KV_STAGES == 12, "staging");

__global__ void __launch_bounds__(384, 1) k_v(const __grid_constant__ KVParams p) {
  extern __shared__ uint8_t smem_raw[];
  const uint32_t sb = (smem_u32(smem_raw) + 1023) & ~1023u;
  const int tid = threadIdx.x, w = tid >> 5, lane = tid & 31;
  const uint32_t full = sb + KV_BAR, empty = full + 8 * KV_STAGES, wfull = empty + 8 * KV_STAGES, wdone = wfull + 8;
  TS(1, 0);
  if (tid == 0) {
    for (int i = 0; i < KV_STAGES; i++) { mbar_init(full + 8 * i, 1); mbar_init(empty + 8 * i, 16); }
    mbar_init(wfull, 1); mbar_init(wdone, 16);
    fence_mbar_init();
  }
  pdl_launch();
  __syncthreads();
  cluster_sync();
  const uint32_t rk = blockIdx.x & 1;
  if (w >= 8) {
    asm volatile("setmaxnreg.dec.sync.aligned.u32 40;");
    if (w == 8 && lane == 0) {
      int st = 0, ph = 1;
      for (int it = 0; it < 16 * 7; it++) {
        const int tile = it / 7, kc = it - tile * 7;
        if (it == KV_WST) mbar_wait(wdone, 0);
        mbar_wait(empty + 8 * st, ph);
        mbar_expect_tx(full + 8 * st, 16384);
        tma2d_mc(sb + st * 16384 + rk * 8192, &p.tmX64, 64 * kc, 128 * tile + 64 * rk, full + 8 * st, 0x3);
        if (++st == KV_STAGES) { st = 0; ph ^= 1; }
      }
    } else if (w == 9) {
      if (lane == 0) {
        mbar_expect_tx(wfull, 8 * 14336);
        flag_wait(&gFlags[F_PRE * 32], 128); fence_proxy_async_global();
        bulk_g2s(sb + KV_WST * 16384, gBt + (size_t)blockIdx.x * 8 * 28 * 128, 8 * 14336, wfull);
      }
      __syncwarp();
      for (int tile = 0; tile < 16; tile++) {
        bar_sync(1 + (tile & 1), 288);
        if (lane == 0) red_release_add(&gFlags[(F_V + tile) * 32], 2);
        __syncwarp();
      }
    }
    __syncwarp();
  } else {
    asm volatile("setmaxnreg.inc.sync.aligned.u32 232;");
    const int tg = blockIdx.x * 8 + w;
    const int h = tg / 28, tf = tg - h * 28;
    uint32_t a[28][4];
    mbar_wait(wfull, 0);
#pragma unroll
    for (int ks = 0; ks < 28; ks++) ldsm4(sb + KV_WST * 16384 + (w * 28 + ks) * 512 + lane * 16, a[ks][0], a[ks][1], a[ks][2], a[ks][3]);
    __syncwarp();
    if (lane < 2) mbar_arrive_remote(mapa(wdone, lane));
    TS(1, 1);
    int st = 0, ph = 0;
    for (int tile = 0; tile < 16; tile++) {
      float acc[64];
      int prev = -1;
#pragma unroll
      for (int kc = 0; kc < 7; kc++) {
        mbar_wait(full + 8 * st, ph);
        wg_fence();
#pragma unroll
        for (int ks = 0; ks < 4; ks++) {
          const int k = kc * 4 + ks;
          wg_rs_n128<0>(acc, a[k][0], a[k][1], a[k][2], a[k][3], make_desc(sb + st * 16384 + ks * 32, 0), k != 0);
        }
        wg_commit();
        if (prev >= 0) { wg_wait<1>(); if (lane < 2) mbar_arrive_remote(mapa(empty + 8 * prev, lane)); }
        prev = st;
        if (++st == KV_STAGES) { st = 0; ph ^= 1; }
      }
      wg_wait<0>();
      reg_fence(acc);
      if (lane < 2) mbar_arrive_remote(mapa(empty + 8 * prev, lane));
#pragma unroll
      for (int sg = 0; sg < 4; sg++)
#pragma unroll
        for (int ks = 0; ks < 2; ks++) {
          const int j0 = 4 * (4 * sg + 2 * ks);
          gVx[(((4 * tile + sg) * NH + h) * 28 + tf) * 64 + ks * 32 + lane] =
              make_uint4(pack_bf16(acc[j0], acc[j0 + 1]), pack_bf16(acc[j0 + 2], acc[j0 + 3]),
                         pack_bf16(acc[j0 + 4], acc[j0 + 5]), pack_bf16(acc[j0 + 6], acc[j0 + 7]));
        }
      bar_arrive(1 + (tile & 1), 288);
      if (tile == 0) TS(1, 2);
    }
    TS(1, 3);
  }
  cluster_sync();
}

struct RParams { CUtensorMap tmX8, tmA; const bf16* mem0; };
#define R_NBR 7
#define R_D0 0
#define R_D1 210
constexpr int NBR = 7;
constexpr int R_X = 0;
constexpr int R_BW = R_X + 3 * 28672;
constexpr int R_VX = R_BW + 7 * (28 - NBR) * 512;
constexpr int R_PART = R_VX + 3 * 7168;
constexpr int R_MEM = R_PART + 8 * 320 * 4;
constexpr int R_RS = R_MEM + 2 * 7296;
constexpr int R_AST = R_BW;
static_assert(R_AST + 2 * 50176 <= R_MEM, "staging");
constexpr int R_P = R_RS + 4096;
constexpr int R_VMS = R_P + 640;
constexpr int R_BAR = R_VMS + 2 * 1792;
constexpr int R_SMEM = R_BAR + 128 + 1024;
constexpr int RB_AG = 0, RB_RS = 8, RB_MF = 16, RB_X = 24, RB_VX = 48, RB_W = 72, RB_A = 80;

#define PROF(i) do { } while (0)
#define PROFV(i, v) do { } while (0)
#define PROF_DECL
#define WT_BEGIN
#define WT_END(x) do { } while (0)
#define WT_DUMP() do { } while (0)
#define PROF_DUMP() do { } while (0)

__device__ __forceinline__ void spin_cycles(int n) {
  if (n > 20) { const uint32_t e = (uint32_t)clock() + n; while ((int32_t)((uint32_t)clock() - e) < 0) { } }
}
__device__ __forceinline__ void r_issue_x(const RParams& p, uint32_t sb, int h, int seg) {
  const int st = seg % 3;
  const uint32_t xb = sb + R_BAR + RB_X + 8 * st;
  mbar_expect_tx(xb, 28672);
  tma2d_mc(sb + R_X + st * 28672 + h * 1024, &p.tmX8, 64 * (h >> 2), 32 * seg + 8 * (h & 3), xb, 0xFFFF);
  if (h < 12) tma2d_mc(sb + R_X + st * 28672 + (h + 16) * 1024, &p.tmX8, 64 * ((h + 16) >> 2), 32 * seg + 8 * (h & 3), xb, 0xFFFF);
}
__device__ __forceinline__ void r_issue_vx(uint32_t sb, int h, int j, int seg) {
  const int st = seg % 3;
  if ((seg & 3) == 0) { flag_wait(&gFlags[(F_V + (seg >> 2)) * 32], 112); fence_proxy_async_global(); }
  mbar_expect_tx(sb + R_BAR + RB_VX + 8 * st, 7168);
  bulk_g2s(sb + R_VX + st * 7168, &gVx[((seg * NH + h) * 28 + 7 * j) * 64], 7168, sb + R_BAR + RB_VX + 8 * st);
}
template <int NT>
__device__ __forceinline__ void r_load_A(uint32_t (&Aw)[NT][7][4], uint32_t sb, int tile0, int lane) {
  const int m = lane >> 3;
  mbar_wait(sb + R_BAR + RB_A, 0);
#pragma unroll
  for (int i = 0; i < NT; i++)
#pragma unroll
    for (int ks = 0; ks < 7; ks++) {
      const int kb = 2 * ks + (m >> 1);
      ldsm4(sb + R_AST + (kb >= 7 ? 50176 - 7 * 128 : 0) + (2 * (tile0 + 4 * i) + (m & 1)) * 896 + kb * 128 + (lane & 7) * 16,
            Aw[i][ks][0], Aw[i][ks][1], Aw[i][ks][2], Aw[i][ks][3]);
    }
}

template <int NT>
__device__ __forceinline__ void r_ts(const uint32_t (&Aw)[NT][7][4], const uint32_t tb, const uint32_t xb, uint32_t (&t0)[NT], uint32_t (&t1)[NT],
                                     float (&sx0)[4], float (&sx1)[4]) {
  uint32_t b[4][4];
  ldsm4(tb, b[0][0], b[0][1], b[0][2], b[0][3]);
  ldsm4(tb + 64, b[1][0], b[1][1], b[1][2], b[1][3]);
  ldsm4(tb + 128, b[2][0], b[2][1], b[2][2], b[2][3]);
  ldsm2(tb + 192, b[3][0], b[3][1]);
  float T[NT][4];
#pragma unroll
  for (int i = 0; i < NT; i++) T[i][0] = T[i][1] = T[i][2] = T[i][3] = 0.f;
#pragma unroll
  for (int i = 0; i < 4; i++) sx0[i] = sx1[i] = 0.f;
#pragma unroll
  for (int ks = 0; ks < 7; ks++) {
    mma16816(T[0], Aw[0][ks][0], Aw[0][ks][1], Aw[0][ks][2], Aw[0][ks][3], b[ks >> 1][(ks & 1) * 2], b[ks >> 1][(ks & 1) * 2 + 1]);
    mma16816(T[1], Aw[1][ks][0], Aw[1][ks][1], Aw[1][ks][2], Aw[1][ks][3], b[ks >> 1][(ks & 1) * 2], b[ks >> 1][(ks & 1) * 2 + 1]);
  }
  uint32_t xa[2][4], xc[2][4];
  ldsm4(xb, xa[0][0], xa[0][1], xa[0][2], xa[0][3]);
  ldsm4(xb + 2048, xc[0][0], xc[0][1], xc[0][2], xc[0][3]);
  ldsm4(xb + 4096, xa[1][0], xa[1][1], xa[1][2], xa[1][3]);
  ldsm4(xb + 4096 + 2048, xc[1][0], xc[1][1], xc[1][2], xc[1][3]);
#pragma unroll
  for (int ks = 0; ks < 7; ks++) {
#pragma unroll
    for (int i = 2; i < NT; i++)
      mma16816(T[i], Aw[i][ks][0], Aw[i][ks][1], Aw[i][ks][2], Aw[i][ks][3], b[ks >> 1][(ks & 1) * 2], b[ks >> 1][(ks & 1) * 2 + 1]);
    if (ks == 1) {
#pragma unroll
      for (int i = 0; i < 2; i++) { t0[i] = movm(pack_bf16(T[i][0], T[i][1])); t1[i] = movm(pack_bf16(T[i][2], T[i][3])); }
    }
    if (ks == 3) { mma16816(sx0, xa[0][0], xa[0][1], xa[0][2], xa[0][3], t0[0], t1[0]); mma16816(sx1, xc[0][0], xc[0][1], xc[0][2], xc[0][3], t0[0], t1[0]); }
    if (ks == 4) {
      ldsm4(xb + 2 * 4096, xa[0][0], xa[0][1], xa[0][2], xa[0][3]);
      ldsm4(xb + 2 * 4096 + 2048, xc[0][0], xc[0][1], xc[0][2], xc[0][3]);
    }
    if (ks == 5) { mma16816(sx0, xa[1][0], xa[1][1], xa[1][2], xa[1][3], t0[1], t1[1]); mma16816(sx1, xc[1][0], xc[1][1], xc[1][2], xc[1][3], t0[1], t1[1]); }
  }
  if (NT == 4) {
    ldsm4(xb + 3 * 4096, xa[1][0], xa[1][1], xa[1][2], xa[1][3]);
    ldsm4(xb + 3 * 4096 + 2048, xc[1][0], xc[1][1], xc[1][2], xc[1][3]);
  }
#pragma unroll
  for (int i = 2; i < NT; i++) { t0[i] = movm(pack_bf16(T[i][0], T[i][1])); t1[i] = movm(pack_bf16(T[i][2], T[i][3])); }
#pragma unroll
  for (int i = 2; i < NT; i++) {
    mma16816(sx0, xa[i & 1][0], xa[i & 1][1], xa[i & 1][2], xa[i & 1][3], t0[i], t1[i]);
    mma16816(sx1, xc[i & 1][0], xc[i & 1][1], xc[i & 1][2], xc[i & 1][3], t0[i], t1[i]);
  }
}
__device__ __forceinline__ void r_store_x(uint32_t pb, const float (&sx0)[4], const float (&sx1)[4]) {
  sts32(pb, __float_as_uint(sx0[0]));            sts32(pb + 160, __float_as_uint(sx0[1]));
  sts32(pb + 32, __float_as_uint(sx0[2]));       sts32(pb + 160 + 32, __float_as_uint(sx0[3]));
  sts32(pb + 64, __float_as_uint(sx1[0]));       sts32(pb + 160 + 64, __float_as_uint(sx1[1]));
  sts32(pb + 96, __float_as_uint(sx1[2]));       sts32(pb + 160 + 96, __float_as_uint(sx1[3]));
}
template <int NT>
__device__ __forceinline__ void r_mkeys(uint32_t mb, uint32_t pb, const uint32_t (&t0)[NT], const uint32_t (&t1)[NT]) {
  uint32_t a[NT][4];
#pragma unroll
  for (int i = 0; i < NT; i++) ldsm4(mb + i * 128, a[i][0], a[i][1], a[i][2], a[i][3]);
  float sa[4] = {0.f, 0.f, 0.f, 0.f}, sc[4] = {0.f, 0.f, 0.f, 0.f};
  mma16816(sa, a[0][0], a[0][1], a[0][2], a[0][3], t0[0], t1[0]);
  mma16816(sc, a[1][0], a[1][1], a[1][2], a[1][3], t0[1], t1[1]);
  mma16816(sa, a[2][0], a[2][1], a[2][2], a[2][3], t0[2], t1[2]);
  if (NT == 4) mma16816(sc, a[NT - 1][0], a[NT - 1][1], a[NT - 1][2], a[NT - 1][3], t0[NT - 1], t1[NT - 1]);
  sts32(pb + 128, __float_as_uint(sa[0] + sc[0])); sts32(pb + 160 + 128, __float_as_uint(sa[1] + sc[1]));
}
__device__ __forceinline__ uint32_t xor_or(uint32_t a, uint32_t b, uint32_t t) {
  uint32_t r; asm("lop3.b32 %0,%1,%2,%3,0x7E;" : "=r"(r) : "r"(a), "r"(b), "r"(t)); return r;
}
__device__ __forceinline__ uint32_t or3(uint32_t a, uint32_t b, uint32_t c) {
  uint32_t r; asm("lop3.b32 %0,%1,%2,%3,0xFE;" : "=r"(r) : "r"(a), "r"(b), "r"(c)); return r;
}
__device__ __forceinline__ uint32_t tag_bad(const uint4& a, const uint4& b, const uint4& c, uint32_t tag) {
  const uint32_t x = or3(xor_or(a.x, a.y, tag), xor_or(a.z, a.w, tag), xor_or(b.x, b.y, tag));
  const uint32_t y = or3(xor_or(b.z, b.w, tag), xor_or(c.x, c.y, tag), xor_or(c.z, c.w, tag));
  return (x | y) & 15u;
}

__device__ __forceinline__ void r_wg0(const uint32_t sb, const int h, const int j, const int w, const int lane) {
  const int r = lane >> 2, c = lane & 3, m = lane >> 3;
  uint32_t Aw[4][7][4];
  r_load_A<4>(Aw, sb, w, lane);
  bar_sync(6, 256);
  TS(2, 1);
  PROF_DECL;
  uint32_t bar = sb + R_BAR;
  uint32_t tb0 = sb + R_MEM + (lane & 7) * 912 + (14 * j + m) * 16;
  uint32_t xb0 = sb + R_X + ((lane & 7) + 8 * (m & 1)) * 128 + (((2 * w + (m >> 1)) ^ (lane & 7)) << 4);
  uint32_t pb = sb + R_PART + (w * 320 + 2 * c * 40 + r) * 4;
  uint32_t mb0 = sb + R_MEM + (lane & 7) * 912 + (2 * w + (m >> 1)) * 16;
  KEEP(bar); KEEP(tb0); KEEP(xb0); KEEP(pb); KEEP(mb0);
  int st = 0, xph = 0;
  for (int s = 0; s < NSEG - 1; s++) {
    const uint32_t pm = (s & 1) * 7296;
    if (s == 10) { TS(2, 2); }
    { WT_BEGIN; mbar_wait(bar + RB_X + 8 * st, xph); WT_END(0); }
    const uint32_t xb = xb0 + st * 28672, tb = tb0 + pm, mb = mb0 + pm;
    if (s > 0) mbar_wait(bar + RB_AG, (s - 1) & 1);
    PROF(0);
    uint32_t t0[4], t1[4]; float sxa[4], sxb[4];
    r_ts<4>(Aw, tb, xb, t0, t1, sxa, sxb);
    r_store_x(pb, sxa, sxb);
    bar_arrive(5, 352);
    PROF(1);
    mbar_wait(bar + RB_MF, s & 1);
    PROF(2);
    r_mkeys<4>(mb, pb, t0, t1);
    bar_arrive(1, 352);
    if (s == 0 && w == 3) {
      if (lane == 0) {
        flag_wait(&gFlags[F_V * 32], 112); fence_proxy_async_global();
        r_issue_vx(sb, h, j, 1); r_issue_vx(sb, h, j, 2);
      }
      __syncwarp();
    }
    PROF(3);
    if (++st == 3) { st = 0; xph ^= 1; }
  }
  PROF_DUMP(); WT_DUMP();
}

__device__ __forceinline__ void r_comm(const RParams& p, const uint32_t sb, const int h, const int j, const int w, const int lane) {
  const int wc = w - 8, t = wc * 32 + lane;
  PROF_DECL;
  uint32_t bar = sb + R_BAR;
  uint32_t mem0s = sb + R_MEM;
  const char* mg = reinterpret_cast<const char*>(gMem) + 8192;
  uint32_t dd[4]; const char* gg[4];
#pragma unroll
  for (int i = 0; i < 4; i++) {
    const int v = min(t + 96 * i, 335), n = v / 42, u = v - n * 42, cb = u + (u >= 14 * j ? 14 : 0);
    dd[i] = n * 912 + cb * 16; gg[i] = mg + ((cb / 14) * 8 + n) * 256 + (cb % 14) * 16;
  }
  uint32_t d0 = dd[0], d1 = dd[1], d2 = dd[2], d3 = dd[3];
  const char *g0 = gg[0], *g1 = gg[1], *g2 = gg[2], *g3 = gg[3];
  KEEP(d0); KEEP(d1); KEEP(d2); KEEP(d3); KEEPP(g0); KEEPP(g1); KEEPP(g2); KEEPP(g3);
  const bool p4 = t < 48;
  const int ql = lane / 10, i4 = lane - 10 * ql, q = 3 * wc + ql;
  const bool act = lane < ((wc < 2) ? 30 : 20), xlane = i4 < 8;
  uint32_t rd = sb + R_PART + (q * 40 + 4 * i4) * 4;
  uint32_t pst = sb + R_P + q * 80 + i4 * 8;
  uint4* so = &gS[h * 320 + (xlane ? q * 8 + i4 : 64 + 2 * q + i4 - 8)];
  const uint32_t* pfp = gMem + blockIdx.x * 32;
  if (wc == 0 && lane == 0) { prefetch_l2(pfp + 2048); prefetch_l2(pfp + 2 * 2048); prefetch_l2(pfp + 3 * 2048); }
  int qlk = ql, j0 = j * 80, j1 = ((j + 1) & 3) * 80, j2 = ((j + 2) & 3) * 80, j3 = ((j + 3) & 3) * 80;
  KEEP(bar); KEEP(mem0s); KEEP(rd); KEEP(pst); KEEPP(so); KEEP(qlk); KEEP(j0); KEEP(j1); KEEP(j2); KEEP(j3);
  uint32_t tag = 1;
  for (int s = 0; s < NSEG; s++) {
    const uint32_t md = mem0s + (s & 1) * 7296;
    if (s > 0) {
      mbar_wait(bar + RB_AG, (s - 1) & 1);
      PROF(0);
      if (wc == 0 && lane == 0 && s < NSEG - 1) mbar_expect_tx(bar + RB_AG, 1792);
      spin_cycles(R_D0);
      WT_BEGIN;
      int guard = 0;
      uint4 v[4];
      v[3] = make_uint4(0, 0, 0, 0);
      while (true) {
        v[0] = ldg_relaxed128(g0); v[1] = ldg_relaxed128(g1); v[2] = ldg_relaxed128(g2);
        if (p4) v[3] = ldg_relaxed128(g3);
        const uint32_t m0 = max(max(v[0].x, v[0].y), max(v[0].z, v[0].w)), m1 = max(max(v[1].x, v[1].y), max(v[1].z, v[1].w));
        const uint32_t m2 = max(max(v[2].x, v[2].y), max(v[2].z, v[2].w)), m3 = max(max(v[3].x, v[3].y), max(v[3].z, v[3].w));
        if (max(max(m0, m1), max(m2, m3)) != ~0u) break;
        if (++guard > (1 << 20)) { GM_ABORT(); break; }
      }
      sts128(md + d0, v[0].x, v[0].y, v[0].z, v[0].w);
      sts128(md + d1, v[1].x, v[1].y, v[1].z, v[1].w);
      sts128(md + d2, v[2].x, v[2].y, v[2].z, v[2].w);
      if (p4) sts128(md + d3, v[3].x, v[3].y, v[3].z, v[3].w);
      g0 += 8192; g1 += 8192; g2 += 8192; g3 += 8192;
      WT_END(0);
      PROFV(8, __reduce_max_sync(~0u, guard) + 100);
    } else if (wc == 0 && lane == 0) {
      mbar_expect_tx(bar + RB_AG, 1792);
    }
    __syncwarp();
    if (lane == 0) mbar_arrive(bar + RB_MF);
    if (blockIdx.x == 0 && t == 0) stg_relaxed32(&gFlags[(F_MEM + s) * 32], 1);
    PROF(1);
    if (s == NSEG - 1) break;
    uint4* sx = so + (s & 1) * (NH * 320);
    uint4 own = make_uint4(0, 0, 0, 0), p1 = own, p2 = own, p3 = own;
#define GM_S8(f) (((__uint_as_float(v0.f) + __uint_as_float(v1.f)) + (__uint_as_float(v2.f) + __uint_as_float(v3.f))) + \
                  ((__uint_as_float(v4.f) + __uint_as_float(v5.f)) + (__uint_as_float(v6.f) + __uint_as_float(v7.f))))
#define GM_REDUCE8() do { \
      uint4 v0 = lds128(rd), v1 = lds128(rd + 1280), v2 = lds128(rd + 2 * 1280), v3 = lds128(rd + 3 * 1280); \
      uint4 v4 = lds128(rd + 4 * 1280), v5 = lds128(rd + 5 * 1280), v6 = lds128(rd + 6 * 1280), v7 = lds128(rd + 7 * 1280); \
      own.x = (__float_as_uint(GM_S8(x)) & ~15u) | tag; own.y = (__float_as_uint(GM_S8(y)) & ~15u) | tag; \
      own.z = (__float_as_uint(GM_S8(z)) & ~15u) | tag; own.w = (__float_as_uint(GM_S8(w)) & ~15u) | tag; \
      GM_PUBLISH(); } while (0)
#define GM_PUBLISH() stg_relaxed128(sx + j0, own.x, own.y, own.z, own.w)
    bar_sync(5, 352);
    if (act && xlane) GM_REDUCE8();
    __syncwarp();
    bar_sync(1, 352);
    PROF(2);
    if (act && !xlane) GM_REDUCE8();
    __syncwarp();
    bar_arrive(4, 224);
#undef GM_REDUCE8
#undef GM_S8
#undef GM_PUBLISH
    if (act) {
      PROF(3);
      spin_cycles(R_D1);
      uint4 a1 = ldg_relaxed128(sx + j1), a2 = ldg_relaxed128(sx + j2), a3 = ldg_relaxed128(sx + j3);
      int guard = 0;
      while (tag_bad(a1, a2, a3, tag) != 0) {
        if (++guard > (1 << 20)) { GM_ABORT(); break; }
        a1 = ldg_relaxed128(sx + j1); a2 = ldg_relaxed128(sx + j2); a3 = ldg_relaxed128(sx + j3);
      }
      p1 = a1; p2 = a2; p3 = a3;
      PROFV(9, guard + 1);
    }
    __syncwarp();
    PROF(4);
    const float e0 = (__uint_as_float(own.x) + __uint_as_float(p2.x)) + (__uint_as_float(p1.x) + __uint_as_float(p3.x));
    const float e1 = (__uint_as_float(own.y) + __uint_as_float(p2.y)) + (__uint_as_float(p1.y) + __uint_as_float(p3.y));
    const float e2 = (__uint_as_float(own.z) + __uint_as_float(p2.z)) + (__uint_as_float(p1.z) + __uint_as_float(p3.z));
    const float e3 = (__uint_as_float(own.w) + __uint_as_float(p2.w)) + (__uint_as_float(p1.w) + __uint_as_float(p3.w));
    int mi = __float_as_int(fmaxf(fmaxf(e0, e1), fmaxf(e2, e3)));
    mi ^= (mi >> 31) & 0x7fffffff;
    if (!act) mi = (int)0x80000000;
    const int m0 = __reduce_max_sync(~0u, qlk == 0 ? mi : (int)0x80000000);
    const int m1 = __reduce_max_sync(~0u, qlk == 1 ? mi : (int)0x80000000);
    const int m2 = __reduce_max_sync(~0u, qlk == 2 ? mi : (int)0x80000000);
    int mm = qlk == 0 ? m0 : (qlk == 1 ? m1 : m2);
    mm ^= (mm >> 31) & 0x7fffffff;
    const float mx = __int_as_float(mm);
    if (act) sts64(pst, pack_bf16(ex2(e0 - mx), ex2(e1 - mx)), pack_bf16(ex2(e2 - mx), ex2(e3 - mx)));
    PROF(5);
    bar_arrive(2, 224);
    if (wc == 0) {
      if (lane == 0 && s + 2 < NSEG - 1) r_issue_x(p, sb, h, s + 2);
      if (lane == 0 && s + 4 < NSEG) prefetch_l2(pfp + (s + 4) * 2048);
    } else if (wc == 1) {
      if (lane == 0 && s > 0 && s + 2 < NSEG - 1) r_issue_vx(sb, h, j, s + 2);
    }
    __syncwarp();
    tag = (tag == 15) ? 1 : tag + 1;
  }
  PROF_DUMP(); WT_DUMP();
}

__device__ __forceinline__ void r_reducer(const uint32_t sb, const int h, const int j, const int w, const int lane) {
  PROF_DECL;
  uint32_t bar = sb + R_BAR;
  const int g = h >> 3, npk = g ? 6 : 8;
  const int u = lane & 7, dg = lane >> 3;
  const bool snd = u < npk, rdl = lane < 4 * npk;
  auto lane2word = [&](int l) { return (g == 0 || l < 16) ? 16 * (l >> 4) + 8 * ((l & 3) >> 1) + 2 * ((l >> 2) & 3) + (l & 1) : 16 + 2 * ((l - 16) >> 1) + (l & 1); };
  auto word2lane = [&](int fw) { return (g == 0 || fw < 16) ? 16 * (fw >> 4) + 4 * ((fw & 7) >> 1) + 2 * ((fw >> 3) & 1) + (fw & 1) : 16 + (fw - 16); };
  uint32_t la0 = sb + R_MEM + (h & 7) * 912 + (112 * j + 64 * g + 8 * u) * 2;
  uint32_t rsa = sb + R_RS + lane * 4;
  uint32_t* gm0 = &gMem[2048 + (j * 8 + (h & 7)) * 64 + 32 * g + lane2word(lane)];
  int sh0 = word2lane(min(4 * u, 31)), sh1 = word2lane(min(4 * u + 1, 31)), sh2 = word2lane(min(4 * u + 2, 31)), sh3 = word2lane(min(4 * u + 3, 31)), dk = 4 * dg;
  uint32_t rsbytes = g ? 1536 : 2048;
  KEEP(bar); KEEP(la0); KEEP(rsa); KEEPP(gm0); KEEP(sh0); KEEP(sh1); KEEP(sh2); KEEP(sh3); KEEP(dk); KEEP(rsbytes);
  for (int s = 0; s < NSEG - 1; s++) {
    const uint32_t la = la0 + (7296 - (s & 1) * 7296);
    const uint32_t ra0 = mapa(la, dk), rb0 = mapa(bar + RB_AG, dk), ra1 = mapa(la, dk + 1), rb1 = mapa(bar + RB_AG, dk + 1);
    const uint32_t ra2 = mapa(la, dk + 2), rb2 = mapa(bar + RB_AG, dk + 2), ra3 = mapa(la, dk + 3), rb3 = mapa(bar + RB_AG, dk + 3);
    mbar_wait(bar + RB_RS, s & 1);
    PROF(8);
    float a0 = 0.f, a1 = 0.f;
    if (rdl) {
      uint32_t t[16];
#pragma unroll
      for (int i = 0; i < 16; i++) t[i] = lds32(rsa + i * 128);
#define GM_LO(i) __uint_as_float(t[i] << 16)
#define GM_HI(i) __uint_as_float(t[i] & 0xffff0000u)
#define GM_S4(F, i) ((F(i) + F(i + 1)) + (F(i + 2) + F(i + 3)))
      a0 = (GM_S4(GM_LO, 0) + GM_S4(GM_LO, 4)) + (GM_S4(GM_LO, 8) + GM_S4(GM_LO, 12));
      a1 = (GM_S4(GM_HI, 0) + GM_S4(GM_HI, 4)) + (GM_S4(GM_HI, 8) + GM_S4(GM_HI, 12));
#undef GM_S4
#undef GM_LO
#undef GM_HI
    }
    const uint32_t wd = pack_bf16(a0, a1);
    if (rdl) stg_relaxed32(gm0, wd);
    const uint32_t w0 = __shfl_sync(~0u, wd, sh0), w1 = __shfl_sync(~0u, wd, sh1), w2 = __shfl_sync(~0u, wd, sh2), w3 = __shfl_sync(~0u, wd, sh3);
    if (snd) {
      st_async16(ra0, w0, w1, w2, w3, rb0);
      st_async16(ra1, w0, w1, w2, w3, rb1);
      st_async16(ra2, w0, w1, w2, w3, rb2);
      st_async16(ra3, w0, w1, w2, w3, rb3);
    }
    gm0 += 2048;
    if (lane == 0 && s + 2 < NSEG) mbar_expect_tx(bar + RB_RS, rsbytes);
    PROF(9);
  }
  PROF_DUMP(); WT_DUMP();
}

template <bool TWO>
__device__ __forceinline__ void r_wg1(const RParams& p, const uint32_t sb, const int h, const int j, const int w, const int lane) {
  const int r = lane >> 2, c = lane & 3, m = lane >> 3, wq = w - 4;
  constexpr int NV = TWO ? 2 : 1;
  uint32_t Aw[3][7][4], Bw[NV][NBR][4];
  uint32_t bws = sb + R_BW + (2 * wq) * (28 - NBR) * 512 + lane * 16;
  {
    const uint32_t* bt = gBt + (h * 28 + 7 * j + 2 * wq) * 28 * 128;
#pragma unroll
    for (int t = 0; t < NV; t++)
#pragma unroll
      for (int kk = 0; kk < NBR; kk++) {
        const uint32_t* q = bt + (t * 28 + 7 * j + kk) * 128 + lane;
        Bw[t][kk][0] = __ldcg(q); Bw[t][kk][1] = __ldcg(q + 32); Bw[t][kk][2] = __ldcg(q + 64); Bw[t][kk][3] = __ldcg(q + 96);
      }
    r_load_A<3>(Aw, sb, 16 + wq, lane);
    bar_sync(6, 256);
    if (lane == 0) {
      const uint32_t wb = sb + R_BAR + RB_W;
      const int n1 = 21 - 7 * j, k1 = 7 * j + 7;
#pragma unroll
      for (int t = 0; t < NV; t++) {
        const uint32_t d = sb + R_BW + (2 * wq + t) * 21 * 512;
        if (n1 > 0) bulk_g2s(d, bt + (t * 28 + k1) * 128, n1 * 512, wb);
        if (j > 0)  bulk_g2s(d + n1 * 512, bt + t * 28 * 128, 7 * j * 512, wb);
      }
    }
    __syncwarp();
  }
  __syncwarp();
  PROF_DECL;
  uint32_t bar = sb + R_BAR;
  uint32_t tb0 = sb + R_MEM + (lane & 7) * 912 + (14 * j + m) * 16;
  uint32_t xb0 = sb + R_X + 4 * 4096 + ((lane & 7) + 8 * (m & 1)) * 128 + (((2 * wq + (m >> 1)) ^ (lane & 7)) << 4);
  uint32_t vb1 = sb + R_MEM + (lane & 7) * 912 + (14 * ((j + 1) & 3) + m) * 16;
  uint32_t vb2 = sb + R_MEM + (lane & 7) * 912 + (14 * ((j + 2) & 3) + m) * 16;
  uint32_t vb3 = sb + R_MEM + (lane & 7) * 912 + (14 * ((j + 3) & 3) + m) * 16;
  uint32_t pb = sb + R_PART + (w * 320 + 2 * c * 40 + r) * 4;
  uint32_t mb0 = sb + R_MEM + (lane & 7) * 912 + (2 * (wq + 16) + (m >> 1)) * 16;
  const int own_r = 2 * c + (r & 1) + (wq >= 2 ? 8 : 0);
  uint32_t raa = mapa(sb + R_RS + h * 128 + (wq == 3 ? 64 + (r >> 1) * 8 : ((wq & 1) * 4 + (r >> 1)) * 16), own_r), rba = mapa(bar + RB_RS, own_r);
  const uint2* gvm = &gVm[(h * 28 + 7 * j) * 32];
  uint32_t vms = sb + R_VMS + wq * 512 + lane * 8;
  uint32_t pa = sb + R_P + (lane & 7) * 80 + (lane >> 3) * 16, pa4 = sb + R_P + (lane & 7) * 80 + 64;
  uint32_t vx0 = sb + R_VX + wq * 2048 + lane * 16;
  KEEP(bar); KEEP(tb0); KEEP(xb0); KEEP(vb1); KEEP(vb2); KEEP(vb3); KEEP(pb); KEEP(mb0); KEEP(bws); KEEP(raa); KEEP(rba);
  KEEPP(gvm); KEEP(pa); KEEP(pa4); KEEP(vx0); KEEP(vms);

  int st = 0, xph = 0;
  for (int s = 0; s < NSEG; s++) {
    const uint32_t pm = (s & 1) * 7296;
    const bool full = s < NSEG - 1;
    if (full) mbar_wait(bar + RB_X + 8 * st, xph);
    const uint32_t xb = xb0 + st * 28672, tb = tb0 + pm;
    if (s > 0) mbar_wait(bar + RB_AG, (s - 1) & 1);
    PROF(0);
    uint32_t t0[3], t1[3];
    if (full) {
      float sxa[4], sxb[4];
      r_ts<3>(Aw, tb, xb, t0, t1, sxa, sxb);
      r_store_x(pb, sxa, sxb);
      bar_arrive(5, 352);
    }
    PROF(1);
    mbar_wait(bar + RB_MF, s & 1);
    if (full) { r_mkeys<3>(mb0 + pm, pb, t0, t1); bar_arrive(1, 352); }
    PROF(2);
    float a0[4] = {0.f, 0.f, 0.f, 0.f}, a1[4] = {0.f, 0.f, 0.f, 0.f}, b0[4] = {0.f, 0.f, 0.f, 0.f}, b1[4] = {0.f, 0.f, 0.f, 0.f};
    {
      uint32_t f[4][4];
      ldsm4(tb, f[0][0], f[0][1], f[0][2], f[0][3]);
      ldsm4(tb + 64, f[1][0], f[1][1], f[1][2], f[1][3]);
      ldsm4(tb + 128, f[2][0], f[2][1], f[2][2], f[2][3]);
      ldsm2(tb + 192, f[3][0], f[3][1]);
#pragma unroll
      for (int kk = 0; kk < 7; kk++) {
        const uint32_t g0 = f[kk >> 1][(kk & 1) * 2], g1 = f[kk >> 1][(kk & 1) * 2 + 1];
        if (kk & 1) { mma16816(a1, Bw[0][kk][0], Bw[0][kk][1], Bw[0][kk][2], Bw[0][kk][3], g0, g1); if (TWO) mma16816(b1, Bw[NV - 1][kk][0], Bw[NV - 1][kk][1], Bw[NV - 1][kk][2], Bw[NV - 1][kk][3], g0, g1); }
        else        { mma16816(a0, Bw[0][kk][0], Bw[0][kk][1], Bw[0][kk][2], Bw[0][kk][3], g0, g1); if (TWO) mma16816(b0, Bw[NV - 1][kk][0], Bw[NV - 1][kk][1], Bw[NV - 1][kk][2], Bw[NV - 1][kk][3], g0, g1); }
      }
    }
    if (s == 0) mbar_wait(bar + RB_W, 0);
    if (full) bar_sync(4, 224);
    float va[4], vb[4];
    {
      uint32_t f[2][4];
      uint4 wa[2][2], wb[2][2];
      ldsm4(vb1 + pm, f[0][0], f[0][1], f[0][2], f[0][3]);
      wa[0][0] = ldsm128(bws); wa[0][1] = ldsm128(bws + 512);
      if (TWO) { wb[0][0] = ldsm128(bws + 21 * 512); wb[0][1] = ldsm128(bws + 22 * 512); }
#pragma unroll
      for (int i = 0; i < 12; i++) {
        const int cur = i & 1, nxt = cur ^ 1;
        if (i + 1 < 12) {
          const int run = (i + 1) >> 2, pos = (i + 1) & 3, u = 7 * run + 2 * pos;
          const uint32_t fa = (run == 0 ? vb1 : run == 1 ? vb2 : vb3) + pm + pos * 64;
          if (pos < 3) {
            ldsm4(fa, f[nxt][0], f[nxt][1], f[nxt][2], f[nxt][3]);
            wa[nxt][0] = ldsm128(bws + u * 512); wa[nxt][1] = ldsm128(bws + (u + 1) * 512);
            if (TWO) { wb[nxt][0] = ldsm128(bws + (21 + u) * 512); wb[nxt][1] = ldsm128(bws + (22 + u) * 512); }
          } else {
            ldsm2(fa, f[nxt][0], f[nxt][1]);
            wa[nxt][0] = ldsm128(bws + u * 512);
            if (TWO) wb[nxt][0] = ldsm128(bws + (21 + u) * 512);
          }
        }
        mma16816(a0, wa[cur][0].x, wa[cur][0].y, wa[cur][0].z, wa[cur][0].w, f[cur][0], f[cur][1]);
        if (TWO) mma16816(b0, wb[cur][0].x, wb[cur][0].y, wb[cur][0].z, wb[cur][0].w, f[cur][0], f[cur][1]);
        if ((i & 3) < 3) {
          mma16816(a1, wa[cur][1].x, wa[cur][1].y, wa[cur][1].z, wa[cur][1].w, f[cur][2], f[cur][3]);
          if (TWO) mma16816(b1, wb[cur][1].x, wb[cur][1].y, wb[cur][1].z, wb[cur][1].w, f[cur][2], f[cur][3]);
        }
      }
#pragma unroll
      for (int i = 0; i < 4; i++) { va[i] = a0[i] + a1[i]; vb[i] = b0[i] + b1[i]; }
    }
    const uint32_t vma0 = pack_bf16(va[0], va[1]), vma1 = pack_bf16(va[2], va[3]);
    const uint32_t vmb0 = pack_bf16(vb[0], vb[1]), vmb1 = pack_bf16(vb[2], vb[3]);
    if (s == 0) {
      float v[NV][4][4];
#pragma unroll
      for (int t = 0; t < NV; t++)
#pragma unroll
        for (int n = 0; n < 4; n++) v[t][n][0] = v[t][n][1] = v[t][n][2] = v[t][n][3] = 0.f;
      const uint32_t xrow = sb + R_X + ((lane & 7) + 8 * (m >> 1)) * 128;
#pragma unroll
      for (int kk = 0; kk < 28; kk++) {
        int ks = 7 * j + kk; if (ks >= 28) ks -= 28;
        const uint32_t xa = xrow + (ks >> 2) * 4096 + (((((2 * ks) & 7) + (m & 1)) ^ (lane & 7)) << 4);
        uint32_t f0, f1, f2, f3, g0, g1, g2, g3;
        ldsm4(xa, f0, f1, f2, f3);
        ldsm4(xa + 2048, g0, g1, g2, g3);
#pragma unroll
        for (int t = 0; t < NV; t++) {
          uint4 a;
          if (kk < NBR) a = make_uint4(Bw[t][kk < NBR ? kk : 0][0], Bw[t][kk < NBR ? kk : 0][1], Bw[t][kk < NBR ? kk : 0][2], Bw[t][kk < NBR ? kk : 0][3]);
          else          a = ldsm128(bws + (t * 21 + kk - NBR) * 512);
          mma16816(v[t][0], a.x, a.y, a.z, a.w, f0, f1);
          mma16816(v[t][1], a.x, a.y, a.z, a.w, f2, f3);
          mma16816(v[t][2], a.x, a.y, a.z, a.w, g0, g1);
          mma16816(v[t][3], a.x, a.y, a.z, a.w, g2, g3);
        }
      }
#pragma unroll
      for (int t = 0; t < NV; t++)
#pragma unroll
        for (int k2 = 0; k2 < 2; k2++)
          sts128(vx0 + t * 1024 + k2 * 512, pack_bf16(v[t][2 * k2][0], v[t][2 * k2][1]), pack_bf16(v[t][2 * k2][2], v[t][2 * k2][3]),
                 pack_bf16(v[t][2 * k2 + 1][0], v[t][2 * k2 + 1][1]), pack_bf16(v[t][2 * k2 + 1][2], v[t][2 * k2 + 1][3]));
      __syncwarp();
    }
    sts64(vms + (s & 1) * 1792, vma0, vma1);
    if (TWO) sts64(vms + (s & 1) * 1792 + 256, vmb0, vmb1);
    fence_proxy_async_smem();
    PROF(3);
    if (!full) bar_sync(3, 128);
    if (full) {
      { WT_BEGIN; mbar_wait(bar + RB_VX + 8 * st, xph); WT_END(0); }
      const uint32_t vx = vx0 + st * 7168;
      const uint4 xa0 = lds128(vx), xa1 = lds128(vx + 512);
      uint4 xb0v = make_uint4(0, 0, 0, 0), xb1v = xb0v;
      if (TWO) { xb0v = lds128(vx + 1024); xb1v = lds128(vx + 1536); }
      bar_sync(2, 224);
      uint32_t q0, q1, q2, q3, q4;
      ldsm4(pa, q0, q1, q2, q3);
      asm volatile("ldmatrix.sync.aligned.m8n8.x1.shared.b16 {%0},[%1];" : "=r"(q4) : "r"(pa4) : "memory");
      PROF(4);
      float oa_[4] = {0.f, 0.f, 0.f, 0.f}, ob_[4] = {0.f, 0.f, 0.f, 0.f}, l[4] = {0.f, 0.f, 0.f, 0.f};
      const uint32_t one = 0x3f803f80u;
      mma16816(l, one, one, one, one, q0, q1);
      mma16816(oa_, xa0.x, xa0.y, xa0.z, xa0.w, q0, q1);
      if (TWO) mma16816(ob_, xb0v.x, xb0v.y, xb0v.z, xb0v.w, q0, q1);
      mma16816(l, one, one, one, one, q2, q3);
      mma16816(oa_, xa1.x, xa1.y, xa1.z, xa1.w, q2, q3);
      if (TWO) mma16816(ob_, xb1v.x, xb1v.y, xb1v.z, xb1v.w, q2, q3);
      mma1688(l, one, one, q4);
      mma1688(oa_, vma0, vma1, q4);
      if (TWO) mma1688(ob_, vmb0, vmb1, q4);
      const float i0 = rcp(l[0]), i1 = rcp(l[1]);
      const bool ev = (r & 1) == 0;
      const uint32_t a02 = pack_bf16(oa_[0] * i0, oa_[2] * i0), a13 = pack_bf16(oa_[1] * i1, oa_[3] * i1);
      const uint32_t ra_ = __shfl_xor_sync(~0u, ev ? a13 : a02, 4);
      const uint32_t aA = ev ? a02 : ra_, aB = ev ? ra_ : a13;
      if (TWO) {
        const uint32_t b02 = pack_bf16(ob_[0] * i0, ob_[2] * i0), b13 = pack_bf16(ob_[1] * i1, ob_[3] * i1);
        const uint32_t rb_ = __shfl_xor_sync(~0u, ev ? b13 : b02, 4);
        const uint32_t bA = ev ? b02 : rb_, bB = ev ? rb_ : b13;
        st_async16(raa, __byte_perm(aA, aB, 0x5410), __byte_perm(aA, aB, 0x7632), __byte_perm(bA, bB, 0x5410), __byte_perm(bA, bB, 0x7632), rba);
      } else {
        st_async8(raa, __byte_perm(aA, aB, 0x5410), __byte_perm(aA, aB, 0x7632), rba);
      }
      PROF(5);
    }
    if (!TWO && lane == 0) {
      if (s > 0) { bulk_wait<0>(); fence_proxy_async_global(); red_relaxed_add(&gFlags[(F_VM + s - 1) * 32], 1); }
      bulk_s2g(gvm, sb + R_VMS + (s & 1) * 1792, 1792);
      bulk_commit();
    }
    if (!TWO) __syncwarp();
    gvm += NH * 28 * 32;
    if (++st == 3) { st = 0; xph ^= 1; }
  }
  if (!TWO && lane == 0) { bulk_wait<0>(); fence_proxy_async_global(); red_relaxed_add(&gFlags[(F_VM + NSEG - 1) * 32], 1); }
  PROF_DUMP(); WT_DUMP();
}

__global__ void __launch_bounds__(384, 1) k_rec(const __grid_constant__ RParams p) {
  extern __shared__ uint8_t smem_raw[];
  const uint32_t sb = (smem_u32(smem_raw) + 1023) & ~1023u;
  const int tid = threadIdx.x, w = tid >> 5, lane = tid & 31;
  uint32_t h; asm("mov.u32 %0,%%cluster_ctarank;" : "=r"(h));
  const int j = blockIdx.x >> 4;
  const uint32_t bar = sb + R_BAR;
  TS(2, 0);
  pdl_launch();
  if (tid == 0) {
    mbar_init(bar + RB_AG, 1); mbar_init(bar + RB_RS, 1); mbar_init(bar + RB_MF, 3); mbar_init(bar + RB_W, 1); mbar_init(bar + RB_A, 1);
    for (int i = 0; i < 3; i++) { mbar_init(bar + RB_X + 8 * i, 1); mbar_init(bar + RB_VX + 8 * i, 1); }
    fence_mbar_init();
    mbar_expect_tx(bar + RB_RS, (h >> 3) ? 1536 : 2048);
    mbar_arrive(bar + RB_VX);
  }
  for (int v = tid; v < 448; v += 384) {
    const int n = v / 56, cb = v - n * 56;
    uint4 t = reinterpret_cast<const uint4*>(p.mem0)[v];
    sts128(sb + R_MEM + n * 912 + cb * 16, t.x, t.y, t.z, t.w);
  }
  __syncthreads();
  cluster_sync();
  if (tid == 256) { r_issue_x(p, sb, h, 0); r_issue_x(p, sb, h, 1); }
  __syncwarp();
  if (tid == 0) {
    mbar_expect_tx(bar + RB_W, 7 * 21 * 512);
    mbar_expect_tx(bar + RB_A, 2 * 50176);
    flag_wait(&gFlags[F_PRE * 32], 128); fence_proxy_async_global();
    tma2d(sb + R_AST, &p.tmA, (14 * j) * 32, h * 56, bar + RB_A);
    tma2d(sb + R_AST + 50176, &p.tmA, (14 * j + 7) * 32, h * 56, bar + RB_A);
  }
  __syncthreads();
  if (w < 4) {
    asm volatile("setmaxnreg.inc.sync.aligned.u32 176;");
    r_wg0(sb, h, j, w, lane);
  } else if (w < 8) {
    asm volatile("setmaxnreg.inc.sync.aligned.u32 232;");
    if (w < 7) r_wg1<true>(p, sb, h, j, w, lane);
    else       r_wg1<false>(p, sb, h, j, w, lane);
  } else {
    asm volatile("setmaxnreg.dec.sync.aligned.u32 96;");
    if (w < 11) r_comm(p, sb, h, j, w, lane);
    else        r_reducer(sb, h, j, w, lane);
  }
  __syncthreads();
  TS(2, 3);
  cluster_sync();
}

struct KQParams { CUtensorMap tmX128, tmW; };
constexpr int KQ_ST = 4, KQ_STAGE = 16384 + 32768;
constexpr int KQ_BAR = KQ_ST * KQ_STAGE;
constexpr int KQ_SMEM = KQ_BAR + 128 + 1024;

__global__ void __launch_bounds__(288, 1) k_qkv(const __grid_constant__ KQParams p) {
  extern __shared__ uint8_t smem_raw[];
  const uint32_t sb = (smem_u32(smem_raw) + 1023) & ~1023u;
  const int tid = threadIdx.x, w = tid >> 5, lane = tid & 31;
  const int tile = blockIdx.x / 6, nc = blockIdx.x - tile * 6;
  const uint32_t full = sb + KQ_BAR, empty = full + 8 * KQ_ST;
  TS(4, 0);
  if (tid == 0) {
    for (int i = 0; i < KQ_ST; i++) { mbar_init(full + 8 * i, 1); mbar_init(empty + 8 * i, 8); }
    fence_mbar_init();
  }
  pdl_launch();
  __syncthreads();
  if (w == 8) {
    if (lane == 0) {
      for (int kc = 0; kc < 7; kc++) {
        const int st = kc % KQ_ST;
        if (kc >= KQ_ST) mbar_wait(empty + 8 * st, 0);
        mbar_expect_tx(full + 8 * st, KQ_STAGE);
        const uint32_t d = sb + st * KQ_STAGE;
        tma2d(d, &p.tmX128, 64 * kc, 128 * tile, full + 8 * st);
        for (int b = 0; b < 4; b++) tma2d(d + 16384 + b * 8192, &p.tmW, 224 * nc + 64 * b, 64 * kc, full + 8 * st);
      }
      flag_wait(&gFlags[F_PRE * 32], 128);
    }
    __syncwarp();
    bar_sync(2, 288);
    if (lane == 0) red_release_add(&gFlags[(F_Q + tile) * 32], 1);
  } else {
    const int wg = w >> 2;
    float acc[112];
    int prev = -1;
    for (int kc = 0; kc < 7; kc++) {
      const int st = kc % KQ_ST;
      mbar_wait(full + 8 * st, (kc / KQ_ST) & 1);
      const uint32_t d = sb + st * KQ_STAGE;
      wg_fence();
#pragma unroll
      for (int ks = 0; ks < 4; ks++)
        wg_ss_n224<0, 1>(acc, make_desc(d + wg * 8192 + ks * 32, 0), make_desc(d + 16384 + ks * 2048, 8192), (kc | ks) != 0);
      wg_commit();
      if (prev >= 0) { wg_wait<1>(); if (lane == 0) mbar_arrive(empty + 8 * prev); }
      prev = st;
    }
    wg_wait<0>();
    reg_fence(acc);
    bar_sync(1, 256);
    const int r = lane >> 2, c = lane & 3;
    const uint32_t row0 = sb + (64 * wg + 16 * (w & 3) + r) * 528;
#pragma unroll
    for (int jj = 0; jj < 28; jj++) {
      const int col = 8 * jj + 2 * c, hl = col / 28, dd = col - 28 * hl;
      const uint32_t a = row0 + hl * 64 + dd * 2;
      sts32(a, pack_bf16(acc[4 * jj], acc[4 * jj + 1]));
      sts32(a + 8 * 528, pack_bf16(acc[4 * jj + 2], acc[4 * jj + 3]));
    }
#pragma unroll
    for (int i = 0; i < 4; i++) {
      const int v = tid + 256 * i;
      sts64(sb + (v >> 3) * 528 + (v & 7) * 64 + 56, 0, 0);
    }
    bar_sync(1, 256);
    uint4* dst = reinterpret_cast<uint4*>(gQKV + ((size_t)(128 * tile) * 48 + 8 * nc) * 32);
#pragma unroll
    for (int i = 0; i < 16; i++) {
      const int v = tid + 256 * i, row = v >> 5, cv = v & 31;
      dst[row * 192 + cv] = lds128(sb + row * 528 + cv * 16);
    }
    bar_arrive(2, 288);
    TS(4, 1);
  }
}

constexpr int KA_ROW = 80;
constexpr int KA_SMEM = 2 * 384 * KA_ROW;
struct KAParams { int dummy; };
__global__ void __launch_bounds__(256) k_attn(const KAParams p) {
  extern __shared__ uint8_t smem_raw[];
  const uint32_t sk = smem_u32(smem_raw), sv = sk + 384 * KA_ROW;
  const int tid = threadIdx.x, w = tid >> 5, lane = tid & 31, r = lane >> 2, c = lane & 3;
  const int tile = blockIdx.x >> 3;
  const int Q0 = 128 * tile;
  TS(5, 0);
  pdl_launch();
  if (tid < 3 && tile - tid >= 0) flag_wait(&gFlags[(F_Q + tile - tid) * 32], 6);
#pragma unroll 1
  for (int hh = 0; hh < 2; hh++) {
  const int h = 2 * (blockIdx.x & 7) + hh;
  __syncthreads();
  for (int i = tid; i < 384 * 4 * 2; i += 256) {
    const int kv = i / 1536, rem = i - kv * 1536, row = rem >> 2, ch = rem & 3;
    const int key = Q0 - 256 + row;
    const uint32_t dst = (kv ? sv : sk) + row * KA_ROW + ch * 16;
    if (key >= 0) cp_async16(dst, gQKV + ((size_t)key * 48 + (kv + 1) * 16 + h) * 32 + ch * 8);
    else sts128(dst, 0, 0, 0, 0);
  }
  const int q0 = Q0 + 16 * w;
  uint32_t qa[2][4];
  {
    const uint32_t* qp = reinterpret_cast<const uint32_t*>(gQKV + ((size_t)(q0 + r) * 48 + h) * 32) + c;
#pragma unroll
    for (int ks = 0; ks < 2; ks++) {
      qa[ks][0] = __ldcg(qp + ks * 8); qa[ks][1] = __ldcg(qp + 8 * 48 * 16 + ks * 8);
      qa[ks][2] = __ldcg(qp + ks * 8 + 4); qa[ks][3] = __ldcg(qp + 8 * 48 * 16 + ks * 8 + 4);
    }
  }
  cp_async_wait_all();
  __syncthreads();
  const float sc = 0.18898223650461358f;
  float o[4][4];
#pragma unroll
  for (int i = 0; i < 4; i++) o[i][0] = o[i][1] = o[i][2] = o[i][3] = 0.f;
  float m0 = -INFINITY, m1 = -INFINITY, l0 = 0.f, l1 = 0.f;
  const int rowbase = 16 * w;
  const int m = lane >> 3;
  const uint32_t kaddr = sk + ((lane & 7) + 8 * (m >> 1)) * KA_ROW + (m & 1) * 16;
  const uint32_t vaddr = sv + ((lane & 7) + 8 * (m & 1)) * KA_ROW + (m >> 1) * 16;
  const int istart = max(0, 16 - (q0 >> 4));
  auto chunk = [&](auto nbc, int ib, bool lowmask, bool diag) {
    constexpr int NB = decltype(nbc)::value;
    float s[2 * NB][4];
#pragma unroll
    for (int b = 0; b < NB; b++) {
      s[2 * b][0] = s[2 * b][1] = s[2 * b][2] = s[2 * b][3] = 0.f;
      s[2 * b + 1][0] = s[2 * b + 1][1] = s[2 * b + 1][2] = s[2 * b + 1][3] = 0.f;
#pragma unroll
      for (int ks = 0; ks < 2; ks++) {
        uint32_t b0, b1, b2, b3;
        ldsm4(kaddr + (rowbase + 16 * (ib + b)) * KA_ROW + ks * 32, b0, b1, b2, b3);
        mma16816(s[2 * b], qa[ks][0], qa[ks][1], qa[ks][2], qa[ks][3], b0, b1);
        mma16816(s[2 * b + 1], qa[ks][0], qa[ks][1], qa[ks][2], qa[ks][3], b2, b3);
      }
    }
    float x0 = -INFINITY, x1 = -INFINITY;
#pragma unroll
    for (int t = 0; t < 2 * NB; t++) {
      const int blk = ib + (t >> 1);
#pragma unroll
      for (int e = 0; e < 4; e += 2) {
        const uint32_t u = pack_bf16(s[t][e], s[t][e + 1]);
        const uint32_t u2 = pack_bf16(__uint_as_float(u << 16) * sc, __uint_as_float(u & 0xffff0000u) * sc);
        s[t][e] = __uint_as_float(u2 << 16) * LOG2E; s[t][e + 1] = __uint_as_float(u2 & 0xffff0000u) * LOG2E;
      }
#pragma unroll
      for (int e = 0; e < 4; e++) {
        float v = s[t][e];
        const int kk = 8 * (t & 1) + 2 * c + (e & 1), qq = r + 8 * (e >> 1);
        if (diag && kk > qq) v = -INFINITY;
        if (lowmask && (blk < istart || (blk == 0 && kk <= qq))) v = -INFINITY;
        s[t][e] = v;
      }
      x0 = fmaxf(x0, fmaxf(s[t][0], s[t][1])); x1 = fmaxf(x1, fmaxf(s[t][2], s[t][3]));
    }
    x0 = fmaxf(x0, __shfl_xor_sync(~0u, x0, 1)); x0 = fmaxf(x0, __shfl_xor_sync(~0u, x0, 2));
    x1 = fmaxf(x1, __shfl_xor_sync(~0u, x1, 1)); x1 = fmaxf(x1, __shfl_xor_sync(~0u, x1, 2));
    const float n0 = fmaxf(m0, x0), n1 = fmaxf(m1, x1);
    const float a0 = ex2(m0 - n0), a1 = ex2(m1 - n1);
    m0 = n0; m1 = n1;
    l0 *= a0; l1 *= a1;
#pragma unroll
    for (int i = 0; i < 4; i++) { o[i][0] *= a0; o[i][1] *= a0; o[i][2] *= a1; o[i][3] *= a1; }
#pragma unroll
    for (int b = 0; b < NB; b++) {
      float e[2][4];
#pragma unroll
      for (int t = 0; t < 2; t++) {
        e[t][0] = ex2(s[2 * b + t][0] - n0); e[t][1] = ex2(s[2 * b + t][1] - n0);
        e[t][2] = ex2(s[2 * b + t][2] - n1); e[t][3] = ex2(s[2 * b + t][3] - n1);
        l0 += e[t][0] + e[t][1]; l1 += e[t][2] + e[t][3];
      }
      const uint32_t p0 = pack_bf16(e[0][0], e[0][1]), p1 = pack_bf16(e[0][2], e[0][3]), p2 = pack_bf16(e[1][0], e[1][1]), p3 = pack_bf16(e[1][2], e[1][3]);
#pragma unroll
      for (int dh = 0; dh < 2; dh++) {
        uint32_t b0, b1, b2, b3;
        ldsm4t(vaddr + (rowbase + 16 * (ib + b)) * KA_ROW + dh * 32, b0, b1, b2, b3);
        mma16816(o[2 * dh], p0, p1, p2, p3, b0, b1);
        mma16816(o[2 * dh + 1], p0, p1, p2, p3, b2, b3);
      }
    }
  };
  chunk(std::integral_constant<int, 1>(), 16, false, true);
  for (int ib = 12; ib >= 0; ib -= 4) {
    if (ib + 3 < istart) break;
    if (ib == 0 || ib < istart) chunk(std::integral_constant<int, 4>(), ib, true, false);
    else chunk(std::integral_constant<int, 4>(), ib, false, false);
  }
  l0 += __shfl_xor_sync(~0u, l0, 1); l0 += __shfl_xor_sync(~0u, l0, 2);
  l1 += __shfl_xor_sync(~0u, l1, 1); l1 += __shfl_xor_sync(~0u, l1, 2);
  const float i0 = 1.0f / l0, i1 = 1.0f / l1;
  uint32_t* op = reinterpret_cast<uint32_t*>(gO + (size_t)(q0 + r) * D_ + h * 28) + c;
#pragma unroll
  for (int i = 0; i < 4; i++) {
    if (i < 3 || c < 2) {
      op[i * 4] = pack_bf16(o[i][0] * i0, o[i][1] * i0);
      op[8 * (D_ / 2) + i * 4] = pack_bf16(o[i][2] * i1, o[i][3] * i1);
    }
  }
  }
  __syncthreads();
  if (tid == 0) red_release_add(&gFlags[(F_O + tile) * 32], 2);
  TS(5, 1);
}

struct KTParams { CUtensorMap tmX128, tmAt, tmO128, tmWo; bf16* out; };
constexpr int KT_X = 0;
constexpr int KT_M = 7 * 16384;
constexpr int KT_W = KT_M + 7 * 4096;
constexpr int KT_NST = 6;
constexpr int KT_BAR = KT_W + KT_NST * 14336;
constexpr int KT_SMEM = KT_BAR + 512 + 1024;
constexpr int KO_ST = 5, KO_STAGE = 16384;
constexpr int KTB_X = 0, KTB_F = 56, KTB_E = 104, KTB_M = 152, KTB_U = 160, KTB_FF = 168, KTB_Q = 200, KTB_OX = 208, KTB_OF = 216, KTB_OE = 256;
constexpr int KF_VX = 0, KF_VM = 16 * 7168, KF_P = KF_VM + 16 * 1792;
#define TF_LAGV 4
constexpr int TF_LAG = TF_LAGV;
constexpr int TF_UNITS = 33 * 16;
__device__ __forceinline__ int tf_decode(int u, int& idx) {
  int b = u >> 4; idx = u & 15;
  if (b < TF_LAG) return b;
  if (b == TF_LAG) return -100;
  const int k = b - TF_LAG - 1;
  if (k < 2 * (16 - TF_LAG)) return (k & 1) ? (TF_LAG + (k >> 1)) : -((k >> 1) + 1);
  return -((16 - TF_LAG) + (k - 2 * (16 - TF_LAG)) + 1);
}

template <int SG>
__device__ __forceinline__ void kt_softmax(const float (&sx)[32], const float (&sm)[8], int seg, int h, int mt, int lane, float gate0, float gate1) {
  const int r = lane >> 2, c = lane & 3;
  float e[4][4], em[2][2];
  float x0 = -INFINITY, x1 = -INFINITY;
#pragma unroll
  for (int t = 0; t < 4; t++)
#pragma unroll
    for (int k = 0; k < 4; k++) {
      const int kk = 8 * t + 2 * c + (k & 1), qi = 16 * mt + r + 8 * (k >> 1);
      e[t][k] = (kk > qi) ? -INFINITY : sx[4 * (4 * SG + t) + k];
      if (k < 2) x0 = fmaxf(x0, e[t][k]); else x1 = fmaxf(x1, e[t][k]);
    }
  em[0][0] = sm[4 * SG]; em[0][1] = sm[4 * SG + 1]; em[1][0] = sm[4 * SG + 2]; em[1][1] = sm[4 * SG + 3];
  x0 = fmaxf(x0, fmaxf(em[0][0], em[0][1])); x1 = fmaxf(x1, fmaxf(em[1][0], em[1][1]));
  x0 = fmaxf(x0, __shfl_xor_sync(~0u, x0, 1)); x0 = fmaxf(x0, __shfl_xor_sync(~0u, x0, 2));
  x1 = fmaxf(x1, __shfl_xor_sync(~0u, x1, 1)); x1 = fmaxf(x1, __shfl_xor_sync(~0u, x1, 2));
  float l0 = 0.f, l1 = 0.f;
#pragma unroll
  for (int t = 0; t < 4; t++) {
    e[t][0] = ex2(e[t][0] - x0); e[t][1] = ex2(e[t][1] - x0); e[t][2] = ex2(e[t][2] - x1); e[t][3] = ex2(e[t][3] - x1);
    l0 += e[t][0] + e[t][1]; l1 += e[t][2] + e[t][3];
  }
  em[0][0] = ex2(em[0][0] - x0); em[0][1] = ex2(em[0][1] - x0); em[1][0] = ex2(em[1][0] - x1); em[1][1] = ex2(em[1][1] - x1);
  l0 += em[0][0] + em[0][1]; l1 += em[1][0] + em[1][1];
  l0 += __shfl_xor_sync(~0u, l0, 1); l0 += __shfl_xor_sync(~0u, l0, 2);
  l1 += __shfl_xor_sync(~0u, l1, 1); l1 += __shfl_xor_sync(~0u, l1, 2);
  const float g0 = __bfloat162float(__float2bfloat16(1.0f - gate0)), g1 = __bfloat162float(__float2bfloat16(1.0f - gate1));
  const float s0 = g0 / l0, s1 = g1 / l1;
  uint32_t* dst = gP + ((size_t)(seg * NH + h) * 2 + mt) * 320;
#pragma unroll
  for (int ks = 0; ks < 2; ks++)
    reinterpret_cast<uint4*>(dst + ks * 128)[lane] =
        make_uint4(pack_bf16(e[2 * ks][0] * s0, e[2 * ks][1] * s0), pack_bf16(e[2 * ks][2] * s1, e[2 * ks][3] * s1),
                   pack_bf16(e[2 * ks + 1][0] * s0, e[2 * ks + 1][1] * s0), pack_bf16(e[2 * ks + 1][2] * s1, e[2 * ks + 1][3] * s1));
  reinterpret_cast<uint2*>(dst + 256)[lane] = make_uint2(pack_bf16(em[0][0] * s0, em[0][1] * s0), pack_bf16(em[1][0] * s1, em[1][1] * s1));
}

__device__ __forceinline__ void kt_consumer(const uint32_t sb, const int tile, const int h, const int w, const int lane, const int nT) {
  const uint32_t bar = sb + KT_BAR;
  const int g = w >> 2;
  float sx[32], sm[8];
  uint32_t ta[4][7][4];
  int st = (28 * nT) % KT_NST, ph = ((28 * nT) / KT_NST) & 1;
#pragma unroll
  for (int nc = 0; nc < 4; nc++) {
    float acc[56];
    int prev = -1;
#pragma unroll 1
    for (int kc = 0; kc < 7; kc++) {
      if (nc == 0) mbar_wait(bar + KTB_X + 8 * kc, nT & 1);
      mbar_wait(bar + KTB_F + 8 * st, ph);
      wg_fence();
#pragma unroll
      for (int ks = 0; ks < 4; ks++)
        wg_ss_n112<0, 0>(acc, make_desc(sb + KT_X + kc * 16384 + g * 8192 + ks * 32, 0), make_desc_ns(sb + KT_W + st * 14336 + ks * 256, 128, 1024), (kc | ks) != 0);
      wg_commit();
      if (prev >= 0) { wg_wait<1>(); if (lane == 0) mbar_arrive(bar + KTB_E + 8 * prev); }
      prev = st;
      if (++st == KT_NST) { st = 0; ph ^= 1; }
    }
    wg_wait<0>();
    if (lane == 0) mbar_arrive(bar + KTB_E + 8 * prev);
    reg_fence(acc);
#pragma unroll
    for (int ks = 0; ks < 7; ks++) {
      ta[nc][ks][0] = pack_bf16(acc[8 * ks], acc[8 * ks + 1]);     ta[nc][ks][1] = pack_bf16(acc[8 * ks + 2], acc[8 * ks + 3]);
      ta[nc][ks][2] = pack_bf16(acc[8 * ks + 4], acc[8 * ks + 5]); ta[nc][ks][3] = pack_bf16(acc[8 * ks + 6], acc[8 * ks + 7]);
    }
    wg_fence();
#pragma unroll
    for (int ks = 0; ks < 7; ks++) {
      const int e0 = 112 * nc + 16 * ks;
      wg_rs_n64<0>(sx, ta[nc][ks][0], ta[nc][ks][1], ta[nc][ks][2], ta[nc][ks][3],
                   make_desc(sb + KT_X + (e0 >> 6) * 16384 + g * 8192 + (e0 & 63) * 2, 0), (nc | ks) != 0);
    }
    wg_commit();
    wg_wait<0>();
  }
  const int wq = w & 3, seg = 4 * tile + 2 * g + (wq >> 1);
  const float gate0 = __uint_as_float(ldg_relaxed32(gG + 32 * seg + 16 * (wq & 1) + (lane >> 2)));
  const float gate1 = __uint_as_float(ldg_relaxed32(gG + 32 * seg + 16 * (wq & 1) + (lane >> 2) + 8));
  mbar_wait(bar + KTB_M, nT & 1);
  wg_fence();
#pragma unroll
  for (int nc = 0; nc < 4; nc++)
#pragma unroll
    for (int ks = 0; ks < 7; ks++) {
      const int e0 = 112 * nc + 16 * ks;
      wg_rs_n16<0>(sm, ta[nc][ks][0], ta[nc][ks][1], ta[nc][ks][2], ta[nc][ks][3],
                   make_desc(sb + KT_M + (e0 >> 6) * 4096 + g * 2048 + (e0 & 63) * 2, 0), (nc | ks) != 0);
    }
  wg_commit();
  wg_wait<0>();
  reg_fence(sx); reg_fence(sm);
  if (wq < 2) kt_softmax<0>(sx, sm, seg, h, wq & 1, lane, gate0, gate1);
  else        kt_softmax<1>(sx, sm, seg, h, wq & 1, lane, gate0, gate1);
  if (w == 0 && lane == 0) sts32(bar + KTB_Q + (nT & 1) * 4, tile);
  __syncwarp();
  bar_arrive(2 + (nT & 1), 288);
}

__device__ __forceinline__ void ko_consumer(const uint32_t sb, const int tile, const int w, const int lane, const int nO) {
  const uint32_t bar = sb + KT_BAR;
  const int g = w >> 2, r = lane >> 2, c = lane & 3;
  int st = (28 * nO) % KO_ST, ph = ((28 * nO) / KO_ST) & 1;
  mbar_wait(bar + KTB_OX, nO & 1);
#pragma unroll 1
  for (int nc = 0; nc < 4; nc++) {
    float acc[56];
    int prev = -1;
#pragma unroll 1
    for (int kc = 0; kc < 7; kc++) {
      mbar_wait(bar + KTB_OF + 8 * st, ph);
      wg_fence();
#pragma unroll
      for (int ks = 0; ks < 4; ks++)
        wg_ss_n112<0, 1>(acc, make_desc(sb + KT_X + kc * 16384 + g * 8192 + ks * 32, 0), make_desc(sb + KT_W + st * KO_STAGE + ks * 2048, 8192), (kc | ks) != 0);
      wg_commit();
      if (prev >= 0) { wg_wait<1>(); if (lane == 0) mbar_arrive(bar + KTB_OE + 8 * prev); }
      prev = st;
      if (++st == KO_ST) { st = 0; ph ^= 1; }
    }
    wg_wait<0>();
    if (lane == 0) mbar_arrive(bar + KTB_OE + 8 * prev);
    reg_fence(acc);
    uint32_t* o0 = reinterpret_cast<uint32_t*>(gA + (size_t)(128 * tile + 64 * g + 16 * (w & 3) + r) * D_ + 112 * nc) + c;
#pragma unroll
    for (int jj = 0; jj < 14; jj++) {
      o0[jj * 4] = pack_bf16(acc[4 * jj], acc[4 * jj + 1]);
      o0[8 * (D_ / 2) + jj * 4] = pack_bf16(acc[4 * jj + 2], acc[4 * jj + 3]);
    }
  }
}

__device__ __forceinline__ void kf_producer(const uint32_t sb, const int seg, const int j) {
  const uint32_t bar = sb + KT_BAR + KTB_FF;
  flag_wait(&gFlags[(F_V + (seg >> 2)) * 32], 112);
  fence_proxy_async_global();
#pragma unroll 1
  for (int h = 0; h < NH; h++) {
    if ((h & 3) == 0) asm volatile("mbarrier.expect_tx.relaxed.cta.shared::cta.b64 [%0],%1;" ::"r"(bar + 8 * (h >> 2)), "r"(4 * 7168) : "memory");
    bulk_g2s(sb + KF_VX + h * 7168, gVx + (((size_t)seg * NH + h) * 28 + 7 * j) * 64, 7168, bar + 8 * (h >> 2));
  }
  flag_wait(&gFlags[(F_VM + seg) * 32], 64);
  fence_proxy_async_global();
#pragma unroll 1
  for (int h = 0; h < NH; h++) {
    if ((h & 3) == 0) asm volatile("mbarrier.expect_tx.relaxed.cta.shared::cta.b64 [%0],%1;" ::"r"(bar + 8 * (h >> 2)), "r"(4 * 1792) : "memory");
    bulk_g2s(sb + KF_VM + h * 1792, gVm + (((size_t)seg * NH + h) * 28 + 7 * j) * 32, 1792, bar + 8 * (h >> 2));
  }
  flag_wait<40>(&gFlags[(F_P + (seg >> 2)) * 32], 16);
  fence_proxy_async_global();
#pragma unroll 1
  for (int g = 0; g < 4; g++) {
    mbar_expect_tx(bar + 8 * g, 4 * 2560);
    bulk_g2s(sb + KF_P + g * 4 * 2560, gP + ((size_t)seg * NH + 4 * g) * 640, 4 * 2560, bar + 8 * g);
  }
}
__device__ __forceinline__ void kf_consumer(bf16* out, const uint32_t sb, const int seg, const int j, const int w, const int lane, const int nF) {
  const int r = lane >> 2, c = lane & 3, tf = 7 * j + w;
  if (w == 0 && lane == 0) flag_wait(&gFlags[(F_A + (seg >> 2)) * 32], 2);
  bar_sync(4, 256);
  if (w == 7) return;
  uint2 av[2][2]; float gv[2][2];
#pragma unroll
  for (int mt = 0; mt < 2; mt++)
#pragma unroll
    for (int hf = 0; hf < 2; hf++) {
      const int tok = 32 * seg + 16 * mt + r + 8 * hf;
      av[mt][hf] = __ldcg(reinterpret_cast<const uint2*>(gA + (size_t)tok * D_ + 16 * tf + 4 * c));
      gv[mt][hf] = __ldcg(gG + tok);
    }
  float acc[2][2][2][4];
#pragma unroll
  for (int e = 0; e < 2; e++)
#pragma unroll
    for (int a = 0; a < 2; a++)
#pragma unroll
      for (int b = 0; b < 2; b++) acc[e][a][b][0] = acc[e][a][b][1] = acc[e][a][b][2] = acc[e][a][b][3] = 0.f;
  const uint32_t vx = sb + KF_VX + w * 1024 + lane * 16, vm = sb + KF_VM + w * 256 + lane * 8, pp = sb + KF_P + lane * 16, ppm = sb + KF_P + 1024 + lane * 8;
#pragma unroll 1
  for (int g = 0; g < 4; g++) {
    mbar_wait(sb + KT_BAR + KTB_FF + 8 * g, nF & 1);
#pragma unroll
    for (int hh = 0; hh < 4; hh++) {
      const int h = 4 * g + hh, e = hh & 1;
      const uint4 x0 = lds128(vx + h * 7168), x1 = lds128(vx + h * 7168 + 512);
      const uint2 m = lds64(vm + h * 1792);
#pragma unroll
      for (int mt = 0; mt < 2; mt++) {
        const uint32_t q = h * 2560 + mt * 1280;
        const uint4 p0 = lds128(pp + q), p1 = lds128(pp + q + 512);
        const uint2 pm = lds64(ppm + q);
        mma16816(acc[e][mt][0], p0.x, p0.y, p0.z, p0.w, x0.x, x0.z);
        mma16816(acc[e][mt][1], p0.x, p0.y, p0.z, p0.w, x0.y, x0.w);
        mma16816(acc[e][mt][0], p1.x, p1.y, p1.z, p1.w, x1.x, x1.z);
        mma16816(acc[e][mt][1], p1.x, p1.y, p1.z, p1.w, x1.y, x1.w);
        mma1688(acc[e][mt][0], pm.x, pm.y, m.x);
        mma1688(acc[e][mt][1], pm.x, pm.y, m.y);
      }
    }
  }
#pragma unroll
  for (int mt = 0; mt < 2; mt++)
#pragma unroll
    for (int hf = 0; hf < 2; hf++) {
      const int tok = 32 * seg + 16 * mt + r + 8 * hf;
      const size_t off = (size_t)tok * D_ + 16 * tf + 4 * c;
      const float g = gv[mt][hf];
      const uint2 a = av[mt][hf];
      const float o0 = g * __uint_as_float(a.x << 16) + (acc[0][mt][0][2 * hf] + acc[1][mt][0][2 * hf]);
      const float o1 = g * __uint_as_float(a.x & 0xffff0000u) + (acc[0][mt][0][2 * hf + 1] + acc[1][mt][0][2 * hf + 1]);
      const float o2 = g * __uint_as_float(a.y << 16) + (acc[0][mt][1][2 * hf] + acc[1][mt][1][2 * hf]);
      const float o3 = g * __uint_as_float(a.y & 0xffff0000u) + (acc[0][mt][1][2 * hf + 1] + acc[1][mt][1][2 * hf + 1]);
      *reinterpret_cast<uint2*>(out + off) = make_uint2(pack_bf16(o0, o1), pack_bf16(o2, o3));
    }
}

__global__ void __launch_bounds__(384, 1) k_tf(const __grid_constant__ KTParams p) {
  extern __shared__ uint8_t smem_raw[];
  const uint32_t sb = (smem_u32(smem_raw) + 1023) & ~1023u;
  const int tid = threadIdx.x, w = tid >> 5, lane = tid & 31;
  const uint32_t bar = sb + KT_BAR;
  if (tid == 0) {
    for (int i = 0; i < 7; i++) mbar_init(bar + KTB_X + 8 * i, 1);
    for (int i = 0; i < KT_NST; i++) { mbar_init(bar + KTB_F + 8 * i, 1); mbar_init(bar + KTB_E + 8 * i, 8); }
    mbar_init(bar + KTB_M, 32);
    for (int i = 0; i < 4; i++) mbar_init(bar + KTB_FF + 8 * i, 1);
    mbar_init(bar + KTB_OX, 1);
    for (int i = 0; i < KO_ST; i++) { mbar_init(bar + KTB_OF + 8 * i, 1); mbar_init(bar + KTB_OE + 8 * i, 8); }
    fence_mbar_init();
  }
  __syncthreads();
  pdl_launch();
  if (w >= 8) {
    asm volatile("setmaxnreg.dec.sync.aligned.u32 24;");
    int nT = 0, nO = 0;
    if (w == 10) {
      for (;; nT++) {
        bar_sync(2 + (nT & 1), 288);
        const int tile = (int)lds32(bar + KTB_Q + (nT & 1) * 4);
        if (tile < 0) break;
        if (lane == 0) red_release_add(&gFlags[(F_P + tile) * 32], 1);
        __syncwarp();
      }
    } else if (w < 10)
    for (int n = 0;; n++) {
      if (tid == 256) sts32(bar + KTB_U + (n & 1) * 4, atomicAdd(&gFlags[F_CTR * 32], 1u));
      bar_sync(1, 320);
      const int u = (int)lds32(bar + KTB_U + (n & 1) * 4);
      if (u >= TF_UNITS) break;
      int idx; const int tile = tf_decode(u, idx);
      if (tile == -100) {
        if (tid == 256) {
          flag_wait(&gFlags[(F_O + idx) * 32], 16);
          fence_proxy_async_global();
          mbar_expect_tx(bar + KTB_OX, 7 * 16384);
#pragma unroll 1
          for (int k = 0; k < 7; k++) tma2d(sb + KT_X + k * 16384, &p.tmO128, 64 * k, 128 * idx, bar + KTB_OX);
#pragma unroll 1
          for (int k = 0; k < 28; k++) {
            const int it = 28 * nO + k, st = it % KO_ST, nc = k / 7, kc = k - 7 * nc;
            if (it >= KO_ST) mbar_wait(bar + KTB_OE + 8 * st, ((it / KO_ST) - 1) & 1);
            mbar_expect_tx(bar + KTB_OF + 8 * st, KO_STAGE);
            const uint32_t d = sb + KT_W + st * KO_STAGE;
            tma2d(d, &p.tmWo, 112 * nc, 64 * kc, bar + KTB_OF + 8 * st);
            tma2d(d + 8192, &p.tmWo, 112 * nc + 64, 64 * kc, bar + KTB_OF + 8 * st);
          }
        }
        __syncwarp();
        nO++;
        continue;
      }
      if (tile < 0) {
        if (tid == 256) kf_producer(sb, 4 * (-tile - 1) + (idx >> 2), idx & 3);
        __syncwarp();
        continue;
      }
      if (w == 8) {
        if (lane == 0) {
          for (int k = 0; k < 28; k++) {
            const int it = 28 * nT + k, st = it % KT_NST, nc = k / 7, kc = k - 7 * nc;
            if (k < 7) { mbar_expect_tx(bar + KTB_X + 8 * k, 16384); tma2d(sb + KT_X + k * 16384, &p.tmX128, 64 * k, 128 * tile, bar + KTB_X + 8 * k); }
            if (it >= KT_NST) mbar_wait(bar + KTB_E + 8 * st, ((it / KT_NST) - 1) & 1);
            mbar_expect_tx(bar + KTB_F + 8 * st, 14336);
            tma2d(sb + KT_W + st * 14336, &p.tmAt, 256 * kc, idx * 56 + 14 * nc, bar + KTB_F + 8 * st);
          }
        }
        __syncwarp();
      } else if (w == 9) {
#pragma unroll 1
        for (int sg = 0; sg < 4; sg++) {
          const uint4* src = reinterpret_cast<const uint4*>(gMem) + (4 * tile + sg) * 512;
          const uint32_t dst = sb + KT_M + sg * 1024;
          int guard = 0;
          if (4 * tile + sg > 0) {
            const uint32_t* canary = &gFlags[(F_MEM + 4 * tile + sg) * 32];
            while (ldg_relaxed32(canary) == 0) { if (++guard > (1 << 21)) { GM_ABORT(); break; } __nanosleep(64); }
            guard = 0;
          }
          while (true) {
            int n = 0, cb = lane;
#pragma unroll 1
            for (int i = 0; i < 14; i++) {
              cp_async16(dst + (cb >> 3) * 4096 + n * 128 + (((cb & 7) ^ n) << 4), src + ((cb / 14) * 8 + n) * 16 + cb % 14);
              cb += 32; if (cb >= 56) { cb -= 56; n++; }
            }
            cp_async_wait_all();
            if (4 * tile + sg == 0) break;
            uint32_t mx = 0;
            n = 0; cb = lane;
#pragma unroll 2
            for (int i = 0; i < 14; i++) {
              const uint4 uu = lds128(dst + (cb >> 3) * 4096 + n * 128 + (((cb & 7) ^ n) << 4));
              mx = max(max(mx, uu.x), max(max(uu.y, uu.z), uu.w));
              cb += 32; if (cb >= 56) { cb -= 56; n++; }
            }
            if (mx != ~0u) break;
            if (++guard > (1 << 19)) { GM_ABORT(); break; }
            __nanosleep(100);
          }
        }
        fence_proxy_async_smem();
        mbar_arrive(bar + KTB_M);
      }
      nT++;
    }
  } else {
    asm volatile("setmaxnreg.inc.sync.aligned.u32 240;");
    int nT = 0, nF = 0, nO = 0;
    for (int n = 0;; n++) {
      bar_sync(1, 320);
      const int u = (int)lds32(bar + KTB_U + (n & 1) * 4);
      if (u >= TF_UNITS) break;
      int idx; const int tile = tf_decode(u, idx);
      if (tile >= 0) {
        TSX(7, tile * 16 + idx, 0);
        uint32_t sbl = sb; KEEP(sbl);
        kt_consumer(sbl, tile, idx, w, lane, nT);
        nT++;
        TSX(7, tile * 16 + idx, 1);
      } else if (tile == -100) {
        TSX(6, idx, 0);
        uint32_t sbl = sb; KEEP(sbl);
        ko_consumer(sbl, idx, w, lane, nO);
        nO++;
        bar_sync(4, 256);
        if (tid == 0) red_release_add(&gFlags[(F_A + idx) * 32], 2);
        TSX(6, idx, 1);
      } else {
        const int tl = -tile - 1, seg = 4 * tl + (idx >> 2);
        TSX(8, seg * 4 + (idx & 3), 0);
        kf_consumer(p.out, sb, seg, idx & 3, w, lane, nF);
        nF++;
        TSX(8, seg * 4 + (idx & 3), 1);
      }
    }
    if (tid == 0) sts32(bar + KTB_Q + (nT & 1) * 4, 0xffffffffu);
    __syncwarp();
    bar_arrive(2 + (nT & 1), 288);
  }
}

typedef CUresult (*PFN_encodeTiled)(CUtensorMap*, CUtensorMapDataType, cuuint32_t, void*, const cuuint64_t*, const cuuint64_t*,
                                    const cuuint32_t*, const cuuint32_t*, CUtensorMapInterleave, CUtensorMapSwizzle,
                                    CUtensorMapL2promotion, CUtensorMapFloatOOBfill);
struct Host {
  PFN_encodeTiled enc = nullptr;
  void *At, *Bt, *QKV, *O, *Aout;
  bool init = false;
};
static Host& host() { static Host* h = nullptr; static char buf[sizeof(Host)] __attribute__((aligned(16))); if (!h) h = new (buf) Host(); return *h; }

static void make_map(CUtensorMap* m, const void* ptr, uint64_t rows, uint64_t cols, uint32_t box_rows, uint32_t box_cols, bool swz) {
  cuuint64_t dims[2] = {cols, rows};
  cuuint64_t strides[1] = {cols * 2};
  cuuint32_t box[2] = {box_cols, box_rows};
  cuuint32_t es[2] = {1, 1};
  host().enc(m, CU_TENSOR_MAP_DATA_TYPE_BFLOAT16, 2, const_cast<void*>(ptr), dims, strides, box, es, CU_TENSOR_MAP_INTERLEAVE_NONE,
             swz ? CU_TENSOR_MAP_SWIZZLE_128B : CU_TENSOR_MAP_SWIZZLE_NONE, CU_TENSOR_MAP_L2_PROMOTION_L2_256B,
             CU_TENSOR_MAP_FLOAT_OOB_FILL_NONE);
}

static void make_map32(CUtensorMap* m, const void* ptr, uint64_t rows, uint64_t cols, uint32_t box_rows, uint32_t box_cols) {
  cuuint64_t dims[2] = {cols, rows};
  cuuint64_t strides[1] = {cols * 4};
  cuuint32_t box[2] = {box_cols, box_rows};
  cuuint32_t es[2] = {1, 1};
  host().enc(m, CU_TENSOR_MAP_DATA_TYPE_UINT32, 2, const_cast<void*>(ptr), dims, strides, box, es, CU_TENSOR_MAP_INTERLEAVE_NONE,
             CU_TENSOR_MAP_SWIZZLE_NONE, CU_TENSOR_MAP_L2_PROMOTION_L2_256B, CU_TENSOR_MAP_FLOAT_OOB_FILL_NONE);
}

static void host_init() {
  Host& H = host();
  if (H.init) return;
  void* fn = nullptr; cudaDriverEntryPointQueryResult qr;
  cudaGetDriverEntryPoint("cuTensorMapEncodeTiled", &fn, cudaEnableDefault, &qr);
  H.enc = (PFN_encodeTiled)fn;
  cudaGetSymbolAddress(&H.At, gAt); cudaGetSymbolAddress(&H.QKV, gQKV);
  cudaGetSymbolAddress(&H.O, gO); cudaGetSymbolAddress(&H.Aout, gA);
  cudaFuncSetAttribute(k_pre, cudaFuncAttributeMaxDynamicSharedMemorySize, KP_SMEM);
  cudaFuncSetAttribute(k_v, cudaFuncAttributeMaxDynamicSharedMemorySize, KV_SMEM);
  cudaFuncSetAttribute(k_rec, cudaFuncAttributeMaxDynamicSharedMemorySize, R_SMEM);
  cudaFuncSetAttribute(k_rec, cudaFuncAttributeNonPortableClusterSizeAllowed, 1);

  cudaFuncSetAttribute(k_qkv, cudaFuncAttributeMaxDynamicSharedMemorySize, KQ_SMEM);
  cudaFuncSetAttribute(k_attn, cudaFuncAttributeMaxDynamicSharedMemorySize, KA_SMEM);
  cudaFuncSetAttribute(k_tf, cudaFuncAttributeMaxDynamicSharedMemorySize, KT_SMEM);
  H.init = true;
}

template <typename P>
static void launch(void (*kern)(P), const P& prm, int grid, int block, int smem, int cluster, bool pdl, cudaStream_t st) {
  cudaLaunchConfig_t cfg = {};
  cfg.gridDim = dim3(grid); cfg.blockDim = dim3(block); cfg.dynamicSmemBytes = smem; cfg.stream = st;
  cudaLaunchAttribute at[2]; int n = 0;
  if (cluster > 1) { at[n].id = cudaLaunchAttributeClusterDimension; at[n].val.clusterDim.x = cluster; at[n].val.clusterDim.y = 1; at[n].val.clusterDim.z = 1; n++; }
  if (pdl) { at[n].id = cudaLaunchAttributeProgrammaticStreamSerialization; at[n].val.programmaticStreamSerializationAllowed = 1; n++; }
  cfg.attrs = at; cfg.numAttrs = n;
  cudaLaunchKernelEx(&cfg, kern, prm);
}

struct In { const bf16 *x, *wqkv, *wo, *mem0, *Wq, *Wk, *Wv, *Wo, *gate; bf16* out; };

static void launch_pre(const In& in, cudaStream_t st) {
  KPParams p;
  make_map(&p.tmWq, in.Wq, 448, 4096, 112, 64, true);
  make_map(&p.tmWk, in.Wk, 448, 4096, 64, 64, true);
  make_map(&p.tmWv, in.Wv, 448, 4096, 112, 64, true);
  make_map(&p.tmWo, in.Wo, 4096, 448, 64, 64, true);
  p.x = in.x; p.gate_w = in.gate; p.mem0 = in.mem0;
  p.W[0] = in.Wk; p.W[1] = in.Wo; p.W[2] = in.Wq; p.W[3] = in.Wv;
  launch(k_pre, p, 128, 384, KP_SMEM, 2, false, st);
}
static void launch_v(const In& in, cudaStream_t st, bool pdl) {
  KVParams p; make_map(&p.tmX64, in.x, S_, D_, 64, 64, true);
  launch(k_v, p, 56, 384, KV_SMEM, 2, pdl, st);
}
static void launch_rec(const In& in, cudaStream_t st, bool pdl) {
  RParams p; make_map(&p.tmX8, in.x, S_, D_, 8, 64, true); p.mem0 = in.mem0;
  make_map32(&p.tmA, host().At, NH * 56, 56 * 32, 56, 224);
  launch(k_rec, p, 64, 384, R_SMEM, 16, pdl, st);
}
static void launch_qkv(const In& in, cudaStream_t st, bool pdl) {
  KQParams p; make_map(&p.tmX128, in.x, S_, D_, 128, 64, true); make_map(&p.tmW, in.wqkv, D_, 3 * D_, 64, 64, true);
  launch(k_qkv, p, 96, 288, KQ_SMEM, 1, pdl, st);
}
static void launch_attn(cudaStream_t st, bool pdl) { KAParams p; p.dummy = 0; launch(k_attn, p, 128, 256, KA_SMEM, 1, pdl, st); }
static void launch_tf(const In& in, cudaStream_t st, bool pdl) {
  KTParams p; p.out = in.out; make_map(&p.tmX128, in.x, S_, D_, 128, 64, true);
  make_map(&p.tmO128, host().O, S_, D_, 128, 64, true); make_map(&p.tmWo, in.wo, D_, D_, 64, 64, true);
  make_map32(&p.tmAt, host().At, NH * 56, 56 * 32, 14, 256);
  launch(k_tf, p, 68, 384, KT_SMEM, 1, pdl, st);
}
}
extern "C" void kernel_launch(void* const* d_in, const int* in_sizes, int n_in, void* d_out, int out_size) {
  using namespace gm;
  host_init();
  In in;
  in.x = (const bf16*)d_in[0]; in.wqkv = (const bf16*)d_in[1]; in.wo = (const bf16*)d_in[2];
  in.mem0 = (const bf16*)d_in[4]; in.Wq = (const bf16*)d_in[5]; in.Wk = (const bf16*)d_in[6];
  in.Wv = (const bf16*)d_in[7]; in.Wo = (const bf16*)d_in[8]; in.gate = (const bf16*)d_in[10];
  in.out = (bf16*)d_out;
  cudaStream_t st = cudaStreamPerThread;
  launch_pre(in, st);
  launch_rec(in, st, true);
  launch_v(in, st, true);
  launch_qkv(in, st, true);
  launch_attn(st, true);
  launch_tf(in, st, true);
}
namespace gm {
}
```
